```python
import torch

def _softmax(x, axis=-1):
    return torch.softmax(x, dim=axis)
def _gelu(x):
    return torch.nn.functional.gelu(x, approximate="tanh")
def _silu(x):
    return torch.nn.functional.silu(x)
def _sigmoid(x):
    return torch.sigmoid(x)
def _layernorm(x, axis=-1, eps=1e-5):
    m = x.mean(dim=axis, keepdim=True)
    v = x.var(dim=axis, keepdim=True, unbiased=False)
    return (x - m) / torch.sqrt(v + eps)
def _scatter_add(tgt, idx, src, axis=0):
    return tgt.clone().index_add_(axis, idx, src)
def _segment_sum(src, seg, n):
    out = torch.zeros((n,) + src.shape[1:], dtype=src.dtype)
    return out.index_add_(0, seg, src)
def _pad(x, pw):
    flat = tuple(v for pair in reversed(pw) for v in pair)
    return torch.nn.functional.pad(x, flat)

kernel_name = 'sequential_preLN__sliding_block__glu_gated_reglu__prompt'

def setup_inputs():

    _w = (lambda a: (lambda t: t.to(torch.bfloat16) if t.is_floating_point() else t)(torch.as_tensor(a)))
    def _A_setup():
        B, S, D = 1, 2048, 512
        return {
            "x": _w((lambda *s: torch.randn(*s, dtype=torch.bfloat16) * 0.05)(B, S, D)),
            "wqkv": _w((lambda *s: torch.randn(*s, dtype=torch.bfloat16) * 0.05)(D, 3 * D)),
            "wo": _w((lambda *s: torch.randn(*s, dtype=torch.bfloat16) * 0.05)(D, D)),
        }
    _A_in = _A_setup()

    def _B_setup():
        B, S, D, F = 1, 2048, 512, 1792
        return {
            "x": _w((lambda *s: torch.randn(*s, dtype=torch.bfloat16) * 0.05)(B, S, D)),
            "W_gate": _w((lambda *s: torch.randn(*s, dtype=torch.bfloat16) * 0.8)(D, F) * (2.0 / D) ** 0.5),
            "W_up": _w((lambda *s: torch.randn(*s, dtype=torch.bfloat16) * 0.8)(D, F) * (2.0 / D) ** 0.5),
            "W_down": _w((lambda *s: torch.randn(*s, dtype=torch.bfloat16) * 0.8)(F, D) * (1.0 / F) ** 0.5),
        }
    _B_in = _B_setup()

    return {
        "A_x": _A_in["x"],
        "A_wqkv": _A_in["wqkv"],
        "A_wo": _A_in["wo"],
        "B_x": _B_in["x"],
        "B_W_gate": _B_in["W_gate"],
        "B_W_up": _B_in["W_up"],
        "B_W_down": _B_in["W_down"],
    }

def reference(A_x, A_wqkv, A_wo, B_x, B_W_gate, B_W_up, B_W_down):
    def _A_ref(x, wqkv, wo):
        B, S, D = x.shape
        H = 32; Dh = D // H; W = 256
        qkv = (lambda x, *d: x.permute(*d))((x @ wqkv).reshape(B, S, 3, H, Dh), 2, 0, 3, 1, 4)
        q, k, v = qkv[0], qkv[1], qkv[2]
        scores = torch.einsum("bhqd,bhkd->bhqk", q, k) * (Dh ** -0.5)
        idx = torch.arange(S)
        mask = (idx[:, None] - idx[None, :] >= 0) & (idx[:, None] - idx[None, :] < W)
        scores = torch.where(mask[None, None], scores, -1e9)
        p = _softmax(scores, axis=-1)
        o = torch.einsum("bhqk,bhkd->bhqd", p, v)
        return (lambda x, *d: x.permute(*d))(o, 0, 2, 1, 3).reshape(B, S, D) @ wo

    def _B_ref(x, W_gate, W_up, W_down):
        gate = torch.einsum("bsd,df->bsf", x, W_gate)
        up = torch.einsum("bsd,df->bsf", x, W_up)
        gate = gate * (lambda x, dt: x.to(dt))(gate > 0, gate.dtype)
        h = gate * up
        return torch.einsum("bsf,fd->bsd", h, W_down)

    x = A_x
    h = x + _A_ref(_layernorm(x, axis=-1), A_wqkv, A_wo)
    h2 = h + _B_ref(_layernorm(h, axis=-1), B_W_gate, B_W_up, B_W_down)
    return h2
```

```cpp
#include <cuda_runtime.h>
#include <cuda.h>
#include <cuda_bf16.h>
#include <stdint.h>

namespace {

constexpr int SEQ = 2048, DM = 512, FF = 1792;
constexpr int NCTA = 128;
constexpr float LN_EPS = 1e-5f;

constexpr uint32_t KB = 1024;
constexpr uint32_t SM_X = 0;
constexpr uint32_t SM_WQ = 0, SM_WV = 64 * KB, SM_WK = 128 * KB;
constexpr uint32_t SM_KV = 128 * KB;
constexpr uint32_t SM_WO = 0;
constexpr uint32_t SM_O = 128 * KB;
constexpr uint32_t SM_HE = 192 * KB;
constexpr uint32_t MISC = 229376;
constexpr uint32_t SM_BAR = MISC;
constexpr uint32_t SM_EPOCH = MISC + 248;
constexpr uint32_t SM_STAT = MISC + 256;
constexpr uint32_t SM_CS = MISC + 256 + 1024;
constexpr uint32_t SMEM_TOTAL = 232448;
__host__ __device__ constexpr uint32_t cslot(int s) { return s == 0 ? 128 * KB : (s == 1 ? 160 * KB : 0u); }
__host__ __device__ constexpr uint32_t aslot(int s) { return s == 0 ? 192 * KB : (uint32_t)s * 32 * KB; }

constexpr int B_FULLA = 0;
constexpr int B_FULLW = 8;
constexpr int B_EMPTYA = 14;
constexpr int B_KV1 = 18, B_KV2 = 19;
constexpr int B_WO = 20;
constexpr int B_CDONE = 21;
constexpr int B_AUX = 22;
constexpr int B_FULLC = 23;
constexpr int B_EMPTYC = 26;
constexpr int B_RECV = 29;
constexpr int B_PEER = 30;

constexpr int NB_CONS = 1, NB_RELKV = 2, NB_RELO = 3, NB_RELH = 4, NB_RELS = 5;

__device__ __align__(16) float g_cs2[16][8][448];
__device__ __align__(128) uint8_t g_kv[NCTA][32768];
__device__ __align__(128) uint8_t g_o[2][NCTA][16384];
__device__ __align__(128) uint8_t g_h[NCTA][16384];
__device__ __align__(128) uint4 g_stat2[2][NCTA][64];
__device__ __align__(128) uint8_t g_p[2][NCTA][3][16384];
__device__ unsigned g_flag[NCTA][32];
__device__ unsigned g_gflag[8][32];
__device__ unsigned g_ticket[32];
#define PROF(i) do {} while (0)
#define PROFT(t, i) do {} while (0)

struct Params {
  CUtensorMap tm_x, tm_qkv, tm_wo, tm_g1, tm_u1, tm_g2, tm_u2, tm_d;
  const __nv_bfloat16 *x, *wqkv, *wo, *wg, *wu, *wd;
  __nv_bfloat16* out;
};

__device__ __forceinline__ void mbar_init(uint32_t b, uint32_t c) { asm volatile("mbarrier.init.shared::cta.b64 [%0], %1;" ::"r"(b), "r"(c) : "memory"); }
__device__ __forceinline__ void mbar_expect(uint32_t b, uint32_t bytes) { asm volatile("mbarrier.arrive.expect_tx.shared::cta.b64 _, [%0], %1;" ::"r"(b), "r"(bytes) : "memory"); }
__device__ __forceinline__ void mbar_arrive(uint32_t b) { asm volatile("mbarrier.arrive.shared::cta.b64 _, [%0];" ::"r"(b) : "memory"); }
__device__ __forceinline__ void mbar_arrive_remote(uint32_t rb) { asm volatile("mbarrier.arrive.relaxed.cluster.shared::cluster.b64 _, [%0];" ::"r"(rb) : "memory"); }
__device__ __forceinline__ uint32_t mapa(uint32_t a, uint32_t cta) { uint32_t r; asm volatile("mapa.shared::cluster.u32 %0, %1, %2;" : "=r"(r) : "r"(a), "r"(cta)); return r; }
__device__ __forceinline__ void mbar_wait(uint32_t b, uint32_t ph) {
  asm volatile("{ .reg .pred p; .reg .u32 n; mov.u32 n, 0x20000;\n"
               "MW%=: mbarrier.try_wait.parity.shared::cta.b64 p, [%0], %1;\n"
               "@!p add.u32 n, n, -1; @!p setp.eq.u32 p, n, 0; @!p bra MW%=; }" ::"r"(b), "r"(ph) : "memory");
}
__device__ __forceinline__ void tma2d(uint32_t dst, const CUtensorMap* m, int c0, int c1, uint32_t bar) {
  asm volatile("cp.async.bulk.tensor.2d.shared::cluster.global.mbarrier::complete_tx::bytes [%0], [%1, {%3, %4}], [%2];" ::"r"(dst), "l"(m), "r"(bar), "r"(c0), "r"(c1) : "memory");
}
__device__ __forceinline__ void tma3d(uint32_t dst, const CUtensorMap* m, int c0, int c1, int c2, uint32_t bar) {
  asm volatile("cp.async.bulk.tensor.3d.shared::cluster.global.mbarrier::complete_tx::bytes [%0], [%1, {%3, %4, %5}], [%2];" ::"r"(dst), "l"(m), "r"(bar), "r"(c0), "r"(c1), "r"(c2) : "memory");
}
__device__ __forceinline__ uint32_t bsub2(uint32_t a, uint32_t b) { uint32_t r; asm("sub.rn.bf16x2 %0, %1, %2;" : "=r"(r) : "r"(a), "r"(b)); return r; }
__device__ __forceinline__ uint32_t bmul2(uint32_t a, uint32_t b) { uint32_t r; asm("mul.rn.bf16x2 %0, %1, %2;" : "=r"(r) : "r"(a), "r"(b)); return r; }
__device__ __forceinline__ void bulk_g2s(uint32_t dst, const void* src, uint32_t bytes, uint32_t bar) {
  asm volatile("cp.async.bulk.shared::cluster.global.mbarrier::complete_tx::bytes [%0], [%1], %2, [%3];" ::"r"(dst), "l"(src), "r"(bytes), "r"(bar) : "memory");
}
__device__ __forceinline__ void bulk_g2s_pair(uint32_t dst, const void* src, uint32_t bytes, uint32_t bar) {
  asm volatile("cp.async.bulk.shared::cluster.global.mbarrier::complete_tx::bytes.multicast::cluster [%0], [%1], %2, [%3], %4;" ::"r"(dst), "l"(src), "r"(bytes), "r"(bar), "h"((uint16_t)3) : "memory");
}
__device__ __forceinline__ void bulk_prefetch(const void* src, uint32_t bytes) { asm volatile("cp.async.bulk.prefetch.L2.global [%0], %1;" ::"l"(src), "r"(bytes) : "memory"); }
__device__ __forceinline__ void prefetch_tm(const CUtensorMap* m) { asm volatile("prefetch.tensormap [%0];" ::"l"(m) : "memory"); }
__device__ __forceinline__ void nb_sync(int id, int n) { asm volatile("bar.sync %0, %1;" ::"r"(id), "r"(n) : "memory"); }
__device__ __forceinline__ void nb_arrive(int id, int n) { asm volatile("bar.arrive %0, %1;" ::"r"(id), "r"(n) : "memory"); }
__device__ __forceinline__ void red_release(unsigned* f) { asm volatile("red.release.gpu.global.add.u32 [%0], 1;" ::"l"(f) : "memory"); }
__device__ __forceinline__ void red_relaxed(unsigned* f) { asm volatile("red.relaxed.gpu.global.add.u32 [%0], 1;" ::"l"(f) : "memory"); }
__device__ __forceinline__ void poll_flag(const unsigned* f, unsigned target) {
  asm volatile("{ .reg .pred p; .reg .u32 n, v; mov.u32 n, 0x20000;\n"
               "PF%=: ld.relaxed.gpu.global.u32 v, [%0]; sub.u32 v, v, %1; setp.ge.s32 p, v, 0;\n"
               "@!p add.u32 n, n, -1; @!p setp.eq.u32 p, n, 0; @!p bra PF%=; }" ::"l"(f), "r"(target) : "memory");
}
__device__ __forceinline__ void fence_async_global() { asm volatile("fence.proxy.async.global;" ::: "memory"); }
__device__ __forceinline__ void fence_acq() { asm volatile("fence.acq_rel.gpu;" ::: "memory"); }
__device__ __forceinline__ void wg_fence() { asm volatile("wgmma.fence.sync.aligned;" ::: "memory"); }
__device__ __forceinline__ void wg_commit() { asm volatile("wgmma.commit_group.sync.aligned;" ::: "memory"); }
template <int N> __device__ __forceinline__ void wg_wait() { asm volatile("wgmma.wait_group.sync.aligned %0;" ::"n"(N) : "memory"); }
__device__ __forceinline__ uint64_t mkdesc(uint32_t addr, uint32_t lbo, uint32_t sbo, uint64_t sw) {
  return (uint64_t)((addr & 0x3FFFF) >> 4) | ((uint64_t)(lbo >> 4) << 16) | ((uint64_t)(sbo >> 4) << 32) | (sw << 62);
}
__device__ __forceinline__ uint32_t pack_bf16(float lo, float hi) { uint32_t r; asm("cvt.rn.bf16x2.f32 %0, %1, %2;" : "=r"(r) : "f"(hi), "f"(lo)); return r; }
__device__ __forceinline__ uint32_t nz(uint32_t v) { uint32_t r; asm("max.u32 %0, %1, 1;" : "=r"(r) : "r"(v)); return r; }
__device__ __forceinline__ uint32_t pack_relu(float lo, float hi) { uint32_t r; asm("cvt.rn.relu.bf16x2.f32 %0, %1, %2;" : "=r"(r) : "f"(hi), "f"(lo)); return r; }
__device__ __forceinline__ float bf_lo(uint32_t v) { return __uint_as_float(v << 16); }
__device__ __forceinline__ float bf_hi(uint32_t v) { return __uint_as_float(v & 0xffff0000u); }
__device__ __forceinline__ float ex2(float x) { float r; asm("ex2.approx.ftz.f32 %0, %1;" : "=f"(r) : "f"(x)); return r; }
__device__ __forceinline__ void sts32(uint32_t a, uint32_t v) { asm volatile("st.shared.u32 [%0], %1;" ::"r"(a), "r"(v) : "memory"); }
__device__ __forceinline__ float2 lds64f(uint32_t a) { float2 v; asm volatile("ld.shared.v2.f32 {%0, %1}, [%2];" : "=f"(v.x), "=f"(v.y) : "r"(a) : "memory"); return v; }
__device__ __forceinline__ void sts64f(uint32_t a, float2 v) { asm volatile("st.shared.v2.f32 [%0], {%1, %2};" ::"r"(a), "f"(v.x), "f"(v.y) : "memory"); }
__device__ __forceinline__ void sts128f(uint32_t a, float4 v) { asm volatile("st.shared.v4.f32 [%0], {%1, %2, %3, %4};" ::"r"(a), "f"(v.x), "f"(v.y), "f"(v.z), "f"(v.w) : "memory"); }
__device__ __forceinline__ float4 lds128f(uint32_t a) { float4 v; asm volatile("ld.shared.v4.f32 {%0, %1, %2, %3}, [%4];" : "=f"(v.x), "=f"(v.y), "=f"(v.z), "=f"(v.w) : "r"(a) : "memory"); return v; }
__device__ __forceinline__ uint4 ldg128_nc(const void* p) { uint4 v; asm volatile("ld.global.nc.v4.u32 {%0, %1, %2, %3}, [%4];" : "=r"(v.x), "=r"(v.y), "=r"(v.z), "=r"(v.w) : "l"(p)); return v; }
__device__ __forceinline__ uint32_t ldg32_nc(const void* p) { uint32_t v; asm volatile("ld.global.nc.u32 %0, [%1];" : "=r"(v) : "l"(p)); return v; }
__device__ __forceinline__ uint32_t ldg32_cg(const void* p) { uint32_t v; asm volatile("ld.global.cg.u32 %0, [%1];" : "=r"(v) : "l"(p) : "memory"); return v; }
__device__ __forceinline__ float4 ldg128f_cg(const void* p) { float4 v; asm volatile("ld.global.cg.v4.f32 {%0, %1, %2, %3}, [%4];" : "=f"(v.x), "=f"(v.y), "=f"(v.z), "=f"(v.w) : "l"(p) : "memory"); return v; }
__device__ __forceinline__ float2 ldg64f_cg(const void* p) { float2 v; asm volatile("ld.global.cg.v2.f32 {%0, %1}, [%2];" : "=f"(v.x), "=f"(v.y) : "l"(p) : "memory"); return v; }
__device__ __forceinline__ void stg32(void* p, uint32_t v) { asm volatile("st.global.u32 [%0], %1;" ::"l"(p), "r"(v) : "memory"); }
__device__ __forceinline__ void stg128_ll(void* p, uint32_t a, uint32_t b, uint32_t c, uint32_t d) {
  asm volatile("{ .reg .b128 t; mov.b128 t, {%1, %2, %3, %4}; st.relaxed.gpu.global.b128 [%0], t; }" ::"l"(p), "r"(nz(a)), "r"(b), "r"(c), "r"(d) : "memory");
}
__device__ __forceinline__ void bulk_s2peer(uint32_t rdst, uint32_t src, uint32_t bytes, uint32_t rbar) {
  asm volatile("cp.async.bulk.shared::cluster.shared::cta.mbarrier::complete_tx::bytes [%0], [%1], %2, [%3];" ::"r"(rdst), "r"(src), "r"(bytes), "r"(rbar) : "memory");
}
__device__ __forceinline__ void stg128(void* p, uint4 v) { asm volatile("st.global.v4.u32 [%0], {%1, %2, %3, %4};" ::"l"(p), "r"(v.x), "r"(v.y), "r"(v.z), "r"(v.w) : "memory"); }
__device__ __forceinline__ void stg64(void* p, uint32_t a, uint32_t b) { asm volatile("st.global.v2.u32 [%0], {%1, %2};" ::"l"(p), "r"(a), "r"(b) : "memory"); }
__device__ __forceinline__ uint4 ldg128_ll(const void* p) {
  uint4 v;
  asm volatile("{ .reg .b128 t; ld.relaxed.gpu.global.b128 t, [%4]; mov.b128 {%0, %1, %2, %3}, t; }" : "=r"(v.x), "=r"(v.y), "=r"(v.z), "=r"(v.w) : "l"(p) : "memory");
  return v;
}
__device__ __forceinline__ void sts128(uint32_t a, uint4 v) { asm volatile("st.shared.v4.u32 [%0], {%1, %2, %3, %4};" ::"r"(a), "r"(v.x), "r"(v.y), "r"(v.z), "r"(v.w) : "memory"); }
__device__ __forceinline__ uint32_t lds32(uint32_t a) { uint32_t v; asm volatile("ld.shared.u32 %0, [%1];" : "=r"(v) : "r"(a) : "memory"); return v; }
__device__ __forceinline__ uint4 lds128(uint32_t a) { uint4 v; asm volatile("ld.shared.v4.u32 {%0, %1, %2, %3}, [%4];" : "=r"(v.x), "=r"(v.y), "=r"(v.z), "=r"(v.w) : "r"(a) : "memory"); return v; }
__device__ __forceinline__ void stg128f(void* p, const float* v) { asm volatile("st.global.v4.f32 [%0], {%1, %2, %3, %4};" ::"l"(p), "f"(v[0]), "f"(v[1]), "f"(v[2]), "f"(v[3]) : "memory"); }
__device__ __forceinline__ void st_async128(uint32_t rdst, const uint32_t* v, uint32_t rbar) {
  asm volatile("st.async.weak.shared::cluster.mbarrier::complete_tx::bytes.v4.b32 [%0], {%1, %2, %3, %4}, [%5];" ::"r"(rdst), "r"(v[0]), "r"(v[1]), "r"(v[2]), "r"(v[3]), "r"(rbar) : "memory");
}
__device__ __forceinline__ void fence_async_smem() { asm volatile("fence.proxy.async.shared::cta;" ::: "memory"); }
__device__ __forceinline__ uint32_t umin3(uint32_t a, uint32_t b, uint32_t c) { return __vimin3_u32(a, b, c); }
template <int N> __device__ __forceinline__ uint32_t min_word(const uint4* v) {
  uint32_t m0 = min(v[0].x, v[1].x), m1 = min(v[2].x, v[3].x);
#pragma unroll
  for (int i = 4; i < N; i += 4) { m0 = umin3(m0, v[i].x, v[i + 1].x); m1 = umin3(m1, v[i + 2].x, v[i + 3].x); }
  return min(m0, m1);
}
template <int N> __device__ __forceinline__ void pin(float (&d)[N]) {
#pragma unroll
  for (int i = 0; i < N; i++) asm volatile("" : "+f"(d[i])::"memory");
}
__device__ __forceinline__ void ldsm4(uint32_t a, uint32_t& r0, uint32_t& r1, uint32_t& r2, uint32_t& r3) {
  asm volatile("ldmatrix.sync.aligned.m8n8.x4.shared.b16 {%0, %1, %2, %3}, [%4];" : "=r"(r0), "=r"(r1), "=r"(r2), "=r"(r3) : "r"(a) : "memory");
}
__device__ __forceinline__ void ldsm4t(uint32_t a, uint32_t& r0, uint32_t& r1, uint32_t& r2, uint32_t& r3) {
  asm volatile("ldmatrix.sync.aligned.m8n8.x4.trans.shared.b16 {%0, %1, %2, %3}, [%4];" : "=r"(r0), "=r"(r1), "=r"(r2), "=r"(r3) : "r"(a) : "memory");
}
__device__ __forceinline__ void mma_acc(float (&c)[4], uint32_t a0, uint32_t a1, uint32_t a2, uint32_t a3, uint32_t b0, uint32_t b1) {
  asm("mma.sync.aligned.m16n8k16.row.col.f32.bf16.bf16.f32 {%0, %1, %2, %3}, {%4, %5, %6, %7}, {%8, %9}, {%0, %1, %2, %3};"
      : "+f"(c[0]), "+f"(c[1]), "+f"(c[2]), "+f"(c[3]) : "r"(a0), "r"(a1), "r"(a2), "r"(a3), "r"(b0), "r"(b1));
}
__device__ __forceinline__ void mma_zero(float* d, uint32_t a0, uint32_t a1, uint32_t a2, uint32_t a3, uint32_t b0, uint32_t b1) {
  asm("mma.sync.aligned.m16n8k16.row.col.f32.bf16.bf16.f32 {%0, %1, %2, %3}, {%4, %5, %6, %7}, {%8, %9}, {%10, %10, %10, %10};"
      : "=f"(d[0]), "=f"(d[1]), "=f"(d[2]), "=f"(d[3]) : "r"(a0), "r"(a1), "r"(a2), "r"(a3), "r"(b0), "r"(b1), "f"(0.f));
}

__device__ __forceinline__ void wgmma_rs_n64(float (&d)[32], uint32_t a0, uint32_t a1, uint32_t a2, uint32_t a3, uint64_t db, int sd) {
  asm volatile("{ .reg .pred p; setp.ne.b32 p, %37, 0;\n"
  "wgmma.mma_async.sync.aligned.m64n64k16.f32.bf16.bf16 {%0, %1, %2, %3, %4, %5, %6, %7, %8, %9, %10, %11, %12, %13, %14, %15, %16, %17, %18, %19, %20, %21, %22, %23, %24, %25, %26, %27, %28, %29, %30, %31}, {%32, %33, %34, %35}, %36, p, 1, 1, 1;\n}"
  : "+f"(d[0]), "+f"(d[1]), "+f"(d[2]), "+f"(d[3]), "+f"(d[4]), "+f"(d[5]), "+f"(d[6]), "+f"(d[7]), "+f"(d[8]), "+f"(d[9]), "+f"(d[10]), "+f"(d[11]), "+f"(d[12]), "+f"(d[13]), "+f"(d[14]), "+f"(d[15]), "+f"(d[16]), "+f"(d[17]), "+f"(d[18]), "+f"(d[19]), "+f"(d[20]), "+f"(d[21]), "+f"(d[22]), "+f"(d[23]), "+f"(d[24]), "+f"(d[25]), "+f"(d[26]), "+f"(d[27]), "+f"(d[28]), "+f"(d[29]), "+f"(d[30]), "+f"(d[31]) : "r"(a0), "r"(a1), "r"(a2), "r"(a3), "l"(db), "r"(sd));
}
__device__ __forceinline__ void wgmma_ss_n128(float (&d)[64], uint64_t da, uint64_t db, int sd) {
  asm volatile("{ .reg .pred p; setp.ne.b32 p, %66, 0;\n"
  "wgmma.mma_async.sync.aligned.m64n128k16.f32.bf16.bf16 {%0, %1, %2, %3, %4, %5, %6, %7, %8, %9, %10, %11, %12, %13, %14, %15, %16, %17, %18, %19, %20, %21, %22, %23, %24, %25, %26, %27, %28, %29, %30, %31, %32, %33, %34, %35, %36, %37, %38, %39, %40, %41, %42, %43, %44, %45, %46, %47, %48, %49, %50, %51, %52, %53, %54, %55, %56, %57, %58, %59, %60, %61, %62, %63}, %64, %65, p, 1, 1, 0, 1;\n}"
  : "+f"(d[0]), "+f"(d[1]), "+f"(d[2]), "+f"(d[3]), "+f"(d[4]), "+f"(d[5]), "+f"(d[6]), "+f"(d[7]), "+f"(d[8]), "+f"(d[9]), "+f"(d[10]), "+f"(d[11]), "+f"(d[12]), "+f"(d[13]), "+f"(d[14]), "+f"(d[15]), "+f"(d[16]), "+f"(d[17]), "+f"(d[18]), "+f"(d[19]), "+f"(d[20]), "+f"(d[21]), "+f"(d[22]), "+f"(d[23]), "+f"(d[24]), "+f"(d[25]), "+f"(d[26]), "+f"(d[27]), "+f"(d[28]), "+f"(d[29]), "+f"(d[30]), "+f"(d[31]), "+f"(d[32]), "+f"(d[33]), "+f"(d[34]), "+f"(d[35]), "+f"(d[36]), "+f"(d[37]), "+f"(d[38]), "+f"(d[39]), "+f"(d[40]), "+f"(d[41]), "+f"(d[42]), "+f"(d[43]), "+f"(d[44]), "+f"(d[45]), "+f"(d[46]), "+f"(d[47]), "+f"(d[48]), "+f"(d[49]), "+f"(d[50]), "+f"(d[51]), "+f"(d[52]), "+f"(d[53]), "+f"(d[54]), "+f"(d[55]), "+f"(d[56]), "+f"(d[57]), "+f"(d[58]), "+f"(d[59]), "+f"(d[60]), "+f"(d[61]), "+f"(d[62]), "+f"(d[63]) : "l"(da), "l"(db), "r"(sd));
}
__device__ __forceinline__ void wgmma_ss_n192(float (&d)[96], uint64_t da, uint64_t db, int sd) {
  asm volatile("{ .reg .pred p; setp.ne.b32 p, %98, 0;\n"
  "wgmma.mma_async.sync.aligned.m64n192k16.f32.bf16.bf16 {%0, %1, %2, %3, %4, %5, %6, %7, %8, %9, %10, %11, %12, %13, %14, %15, %16, %17, %18, %19, %20, %21, %22, %23, %24, %25, %26, %27, %28, %29, %30, %31, %32, %33, %34, %35, %36, %37, %38, %39, %40, %41, %42, %43, %44, %45, %46, %47, %48, %49, %50, %51, %52, %53, %54, %55, %56, %57, %58, %59, %60, %61, %62, %63, %64, %65, %66, %67, %68, %69, %70, %71, %72, %73, %74, %75, %76, %77, %78, %79, %80, %81, %82, %83, %84, %85, %86, %87, %88, %89, %90, %91, %92, %93, %94, %95}, %96, %97, p, 1, 1, 0, 1;\n}"
  : "+f"(d[0]), "+f"(d[1]), "+f"(d[2]), "+f"(d[3]), "+f"(d[4]), "+f"(d[5]), "+f"(d[6]), "+f"(d[7]), "+f"(d[8]), "+f"(d[9]), "+f"(d[10]), "+f"(d[11]), "+f"(d[12]), "+f"(d[13]), "+f"(d[14]), "+f"(d[15]), "+f"(d[16]), "+f"(d[17]), "+f"(d[18]), "+f"(d[19]), "+f"(d[20]), "+f"(d[21]), "+f"(d[22]), "+f"(d[23]), "+f"(d[24]), "+f"(d[25]), "+f"(d[26]), "+f"(d[27]), "+f"(d[28]), "+f"(d[29]), "+f"(d[30]), "+f"(d[31]), "+f"(d[32]), "+f"(d[33]), "+f"(d[34]), "+f"(d[35]), "+f"(d[36]), "+f"(d[37]), "+f"(d[38]), "+f"(d[39]), "+f"(d[40]), "+f"(d[41]), "+f"(d[42]), "+f"(d[43]), "+f"(d[44]), "+f"(d[45]), "+f"(d[46]), "+f"(d[47]), "+f"(d[48]), "+f"(d[49]), "+f"(d[50]), "+f"(d[51]), "+f"(d[52]), "+f"(d[53]), "+f"(d[54]), "+f"(d[55]), "+f"(d[56]), "+f"(d[57]), "+f"(d[58]), "+f"(d[59]), "+f"(d[60]), "+f"(d[61]), "+f"(d[62]), "+f"(d[63]), "+f"(d[64]), "+f"(d[65]), "+f"(d[66]), "+f"(d[67]), "+f"(d[68]), "+f"(d[69]), "+f"(d[70]), "+f"(d[71]), "+f"(d[72]), "+f"(d[73]), "+f"(d[74]), "+f"(d[75]), "+f"(d[76]), "+f"(d[77]), "+f"(d[78]), "+f"(d[79]), "+f"(d[80]), "+f"(d[81]), "+f"(d[82]), "+f"(d[83]), "+f"(d[84]), "+f"(d[85]), "+f"(d[86]), "+f"(d[87]), "+f"(d[88]), "+f"(d[89]), "+f"(d[90]), "+f"(d[91]), "+f"(d[92]), "+f"(d[93]), "+f"(d[94]), "+f"(d[95]) : "l"(da), "l"(db), "r"(sd));
}

__device__ __forceinline__ void acc8(float (&s)[8], uint4 v) {
  s[0] += bf_lo(v.x); s[1] += bf_hi(v.x); s[2] += bf_lo(v.y); s[3] += bf_hi(v.y);
  s[4] += bf_lo(v.z); s[5] += bf_hi(v.z); s[6] += bf_lo(v.w); s[7] += bf_hi(v.w);
}

__device__ __forceinline__ void mma_c4(float* d, const uint32_t (&q)[4], uint32_t b0, uint32_t b1, const float (&c)[4]) {
  asm("mma.sync.aligned.m16n8k16.row.col.f32.bf16.bf16.f32 {%0, %1, %2, %3}, {%4, %5, %6, %7}, {%8, %9}, {%10, %11, %12, %13};"
      : "=f"(d[0]), "=f"(d[1]), "=f"(d[2]), "=f"(d[3])
      : "r"(q[0]), "r"(q[1]), "r"(q[2]), "r"(q[3]), "r"(b0), "r"(b1), "f"(c[0]), "f"(c[1]), "f"(c[2]), "f"(c[3]));
}
__device__ __forceinline__ void sblock(float (&s)[8], const uint32_t (&q)[4], uint32_t ka, const float (&c)[4]) {
  uint32_t k0, k1, k2, k3;
  ldsm4(ka, k0, k1, k2, k3);
  mma_c4(&s[0], q, k0, k1, c);
  mma_c4(&s[4], q, k2, k3, c);
}
__device__ __forceinline__ void expack(const float (&s)[8], uint32_t (&p)[4]) {
  p[0] = pack_bf16(ex2(s[0]), ex2(s[1])); p[1] = pack_bf16(ex2(s[2]), ex2(s[3]));
  p[2] = pack_bf16(ex2(s[4]), ex2(s[5])); p[3] = pack_bf16(ex2(s[6]), ex2(s[7]));
}
__device__ __forceinline__ void pvblock(const uint32_t (&p)[4], uint32_t va, float (&o0)[4], float (&o1)[4], float (&l)[4]) {
  const uint32_t ONES = 0x3f803f80u;
  uint32_t v0, v1, v2, v3;
  ldsm4t(va, v0, v1, v2, v3);
  mma_acc(l, p[0], p[1], p[2], p[3], ONES, ONES);
  mma_acc(o0, p[0], p[1], p[2], p[3], v0, v1);
  mma_acc(o1, p[0], p[1], p[2], p[3], v2, v3);
}

__device__ __forceinline__ void attention(uint32_t sb, const uint32_t (&qf)[4][4], int b, int warp  , int lane, uint8_t* go) {
  const int g = lane >> 2, q4 = lane & 3, mi = lane >> 3;
  const int tmin = max(0, 16 - 8 * b - warp), tl0 = max(1, tmin);
  const uint32_t kaddr = sb + SM_KV + (2 * warp + (mi >> 1)) * 2048 + (mi & 1) * 128 + (lane & 7) * 16;
  const uint32_t vaddr = sb + SM_KV + (2 * warp + (mi & 1)) * 2048 + (8 + (mi >> 1)) * 128 + (lane & 7) * 16;
  const bool pA = (2 * q4 <= g), pB = (2 * q4 + 1 <= g);
  const uint32_t mk = (pA ? 0x0000ffffu : 0u) | (pB ? 0xffff0000u : 0u);
  const uint32_t ONES = 0x3f803f80u;
  const int twait2 = (b >= 2) ? 8 - warp : -1, twait1 = (b >= 1) ? 16 - warp : -1;
  float o0[4][4], o1[4][4], l[4][4], c[4][4];
#pragma unroll
  for (int h = 0; h < 4; h++) {
    float d[4];
    uint32_t k0, k1, k2, k3;
    ldsm4(kaddr + h * 256 + 16 * 4096, k0, k1, k2, k3);
    mma_zero(d, qf[h][0], qf[h][1], qf[h][2], qf[h][3], k0, k1);
    c[h][0] = __shfl_sync(0xffffffffu, -d[0], lane & 28); c[h][2] = __shfl_sync(0xffffffffu, -d[2], lane & 28);
    c[h][1] = __shfl_sync(0xffffffffu, -d[0], 0, 4); c[h][3] = __shfl_sync(0xffffffffu, -d[2], 0, 4);
  }
#pragma unroll 1
  for (int attempt = 0; attempt < 2; attempt++) {
#pragma unroll
    for (int h = 0; h < 4; h++)
#pragma unroll
      for (int e = 0; e < 4; e++) { o0[h][e] = 0.f; o1[h][e] = 0.f; l[h][e] = 0.f; }
    float sc[8], pe[8];
    uint32_t pp[4];
#pragma unroll
    for (int e = 0; e < 8; e++) pe[e] = 0.f;
    if (twait1 == 16) mbar_wait(sb + SM_BAR + B_KV1 * 8, 0);
    sblock(sc, qf[0], kaddr + 15 * 4096, c[0]);
    uint32_t ka = kaddr + 15 * 4096, va = vaddr + 15 * 4096;
#pragma unroll 1
    for (int t = 15; t >= tl0; t--) {
      if (t == twait1 || t == twait2) mbar_wait(sb + SM_BAR + (t == twait1 ? B_KV1 : B_KV2) * 8, 0);
      float s1[8], s2[8], s3[8];
      uint32_t p[4];
      sblock(s1, qf[1], ka + 256, c[1]);
      pp[0] = pack_bf16(pe[0], pe[1]); pp[1] = pack_bf16(pe[2], pe[3]); pp[2] = pack_bf16(pe[4], pe[5]); pp[3] = pack_bf16(pe[6], pe[7]);
      pvblock(pp, va + 4096 + 768, o0[3], o1[3], l[3]);
      expack(sc, p);
      sblock(s2, qf[2], ka + 512, c[2]);
      pvblock(p, va, o0[0], o1[0], l[0]);
      expack(s1, p);
      sblock(s3, qf[3], ka + 768, c[3]);
      pvblock(p, va + 256, o0[1], o1[1], l[1]);
      expack(s2, p);
      sblock(sc, qf[0], ka - 4096, c[0]);
      pvblock(p, va + 512, o0[2], o1[2], l[2]);
#pragma unroll
      for (int e = 0; e < 8; e++) pe[e] = ex2(s3[e]);
      ka -= 4096; va -= 4096;
    }
    pp[0] = pack_bf16(pe[0], pe[1]); pp[1] = pack_bf16(pe[2], pe[3]); pp[2] = pack_bf16(pe[4], pe[5]); pp[3] = pack_bf16(pe[6], pe[7]);
    pvblock(pp, va + 4096 + 768, o0[3], o1[3], l[3]);
    bool ok = true;
#pragma unroll
    for (int h = 0; h < 4; h++) {
      float d[8], tl[8];
      sblock(d, qf[h], kaddr + h * 256 + 16 * 4096, c[h]);
      sblock(tl, qf[h], kaddr + h * 256, c[h]);
      if (tmin > 0) {
#pragma unroll
        for (int e = 0; e < 8; e++) tl[e] = -INFINITY;
      }
      const uint32_t p0 = pack_bf16(ex2(pA ? d[0] : tl[0]), ex2(pB ? d[1] : tl[1])), p1 = pack_bf16(ex2(d[2]), ex2(d[3]));
      const uint32_t p2 = pack_bf16(ex2(tl[4]), ex2(tl[5])), p3 = pack_bf16(ex2(pA ? d[6] : tl[6]), ex2(pB ? d[7] : tl[7]));
      mma_acc(l[h], p0, p1, p2, p3, ONES, ONES);
      uint32_t v0, v1, v2, v3;
      ldsm4t(vaddr + h * 256 + 16 * 4096, v0, v1, v2, v3);
      mma_acc(o0[h], p0 & mk, p1, 0u, p3 & mk, v0, v1); mma_acc(o1[h], p0 & mk, p1, 0u, p3 & mk, v2, v3);
      ldsm4t(vaddr + h * 256, v0, v1, v2, v3);
      mma_acc(o0[h], p0 & ~mk, 0u, p2, p3 & ~mk, v0, v1); mma_acc(o1[h], p0 & ~mk, 0u, p2, p3 & ~mk, v2, v3);
      ok = ok && (l[h][0] <= 1.0e9f) && (l[h][2] <= 1.0e9f);
    }
    if (__builtin_expect(attempt == 1 || __all_sync(0xffffffffu, ok), 1)) break;
    const float z[4] = {0.f, 0.f, 0.f, 0.f};
#pragma unroll
    for (int h = 0; h < 4; h++) { c[h][0] = -INFINITY; c[h][2] = -INFINITY; }
#pragma unroll 1
    for (int t = 16; t >= tmin; t--) {
      const bool a = (t == 16) ? pA : (t != 0 || !pA), bb = (t == 16) ? pB : (t != 0 || !pB);
#pragma unroll
      for (int h = 0; h < 4; h++) {
        float d[8];
        sblock(d, qf[h], kaddr + h * 256 + t * 4096, z);
        if (a) { c[h][0] = fmaxf(c[h][0], d[0]); c[h][2] = fmaxf(c[h][2], d[6]); }
        if (bb) { c[h][0] = fmaxf(c[h][0], d[1]); c[h][2] = fmaxf(c[h][2], d[7]); }
        if (t != 0) c[h][2] = fmaxf(c[h][2], fmaxf(d[2], d[3]));
        if (t != 16) c[h][0] = fmaxf(c[h][0], fmaxf(d[4], d[5]));
      }
    }
#pragma unroll
    for (int h = 0; h < 4; h++) {
      float m0 = c[h][0], m1 = c[h][2];
      m0 = fmaxf(m0, __shfl_xor_sync(0xffffffffu, m0, 1)); m1 = fmaxf(m1, __shfl_xor_sync(0xffffffffu, m1, 1));
      m0 = fmaxf(m0, __shfl_xor_sync(0xffffffffu, m0, 2)); m1 = fmaxf(m1, __shfl_xor_sync(0xffffffffu, m1, 2));
      c[h][0] = -m0; c[h][1] = -m0; c[h][2] = -m1; c[h][3] = -m1;
    }
  }
#pragma unroll
  for (int h = 0; h < 4; h++) {
    float i0, i1;
    asm("rcp.approx.ftz.f32 %0, %1;" : "=f"(i0) : "f"(l[h][0]));
    asm("rcp.approx.ftz.f32 %0, %1;" : "=f"(i1) : "f"(l[h][2]));
    stg128_ll(go + h * 512, pack_bf16(o0[h][0] * i0, o0[h][1] * i0), pack_bf16(o0[h][2] * i1, o0[h][3] * i1),
              pack_bf16(o1[h][0] * i0, o1[h][1] * i0), pack_bf16(o1[h][2] * i1, o1[h][3] * i1));
  }
}

__device__ __forceinline__ void reglu_block(const float* ag, const float* au, uint32_t cs_addr, float m0, float m1, uint32_t& lo, uint32_t& hi) {
  const float4 cs = lds128f(cs_addr);
  lo = bmul2(pack_relu(ag[0] - m0 * cs.x, ag[1] - m0 * cs.y), pack_bf16(au[0] - m0 * cs.z, au[1] - m0 * cs.w));
  hi = bmul2(pack_relu(ag[2] - m1 * cs.x, ag[3] - m1 * cs.y), pack_bf16(au[2] - m1 * cs.z, au[3] - m1 * cs.w));
}

__global__ void __launch_bounds__(384, 1) __cluster_dims__(2, 1, 1) fused_block_kernel(const __grid_constant__ Params p) {
  extern __shared__ __align__(1024) uint8_t smem[];
  uint32_t sb = (uint32_t)__cvta_generic_to_shared(smem);
#define NEW_PHASE() asm volatile("" : "+r"(sb))
  const int tid = threadIdx.x, warp = __shfl_sync(0xffffffffu, tid >> 5, 0), lane = tid & 31;
  const int cta = blockIdx.x, b = cta >> 3, j = cta & 7;
  const int kb0 = j & 6;
  const int hf = j & 1, pi = j >> 1;
  auto bar = [&](int i) { return sb + SM_BAR + i * 8; };

  auto opaque = [](int v) { asm volatile("" : "+r"(v)); return v; };
  if (opaque(warp >> 3)) {
    asm volatile("setmaxnreg.dec.sync.aligned.u32 40;");
    if (opaque(warp == 8)) {
      if (lane == 0) PROF(0);
      if (lane == 0) {
#pragma unroll
        for (int i = 0; i < 4; i++) mbar_init(bar(i), 1);
        fence_async_smem();
        PROF(4);
#pragma unroll
        for (int kb = 0; kb < 8; kb++) {
          if ((kb & 1) == 0) mbar_expect(bar(B_FULLA + (kb >> 1)), 32768);
          tma2d(sb + SM_X + kb * 16384, &p.tm_x, kb * 64, b * 128, bar(B_FULLA + (kb >> 1)));
        }
        PROF(10);
#pragma unroll
        for (int i = 4; i < 31; i++) mbar_init(bar(i), ((0x5C23C000u >> i) & 1) ? 8 : (i == B_AUX ? 3 : 1));
        asm volatile("fence.mbarrier_init.release.cluster;" ::: "memory");
        fence_async_smem();
      }
      __syncwarp();
      nb_arrive(0, 384);
      asm volatile("barrier.cluster.arrive.relaxed.aligned;" ::: "memory");
      unsigned epoch = 0;
      if (lane == 0) {
        PROF(17);
#pragma unroll 1
        for (int c = 0; c < 6; c++) {
          if (c == 2) {
            mbar_expect(bar(B_RECV), 16384);
            bulk_prefetch((const uint8_t*)p.wqkv + cta * 12288, 12288);
            epoch = atomicAdd(&g_ticket[0], 1u) / NCTA;
            sts32(sb + SM_EPOCH, epoch);
            mbar_wait(bar(B_CDONE), 0);
          }
          mbar_expect(bar(B_FULLW + c), 32768);
          tma2d(sb + SM_WK - (c >> 1) * 65536 + (c & 1) * 32768, &p.tm_qkv, (c < 4 ? 512 + (c >> 1) * 512 : 0) + j * 64, (c & 1) * 256, bar(B_FULLW + c));
        }
        bulk_prefetch((const uint8_t*)p.wo + cta * 4096, 4096);
        bulk_prefetch((const uint8_t*)p.wg + cta * 14336, 14336);
        bulk_prefetch((const uint8_t*)p.wu + cta * 14336, 14336);
        bulk_prefetch((const uint8_t*)p.wd + cta * 14336, 14336);
#pragma unroll
        for (int i = 0; i < 6; i++) prefetch_tm(&p.tm_wo + i);
        mbar_wait(bar(B_CDONE), 1);
      }
      epoch = __shfl_sync(0xffffffffu, epoch, 0);
      if (lane == 0) {
#pragma unroll
        for (int i = 0; i < 2; i++)
          if (b > i) {
            mbar_expect(bar(B_KV1 + i), 32768);
            poll_flag(&g_flag[cta - 8 - 8 * i][0], epoch + 1);
            fence_async_global();
            bulk_g2s(sb + SM_KV + (1 - i) * 32768, g_kv[cta - 8 - 8 * i], 32768, bar(B_KV1 + i));
            if (i == 0) PROF(20);
          }
        mbar_expect(bar(B_WO), 131072);
        mbar_wait(bar(B_CDONE), 0);
#pragma unroll
        for (int c = 0; c < 4; c++) tma2d(sb + SM_WO + c * 32768, &p.tm_wo, kb0 * 64 + (c >> 1) * 64, (c & 1) * 256, bar(B_WO));
        mbar_expect(bar(B_FULLA + 4), 32768);
        mbar_expect(bar(B_FULLA + 5), 32768);
        mbar_wait(bar(B_CDONE), 1);
      }
      __syncwarp();
      if (lane < 8) poll_flag(&g_flag[b * 8 + lane][1], 8 * (epoch + 1));
      __syncwarp();
      if (lane == 0) {
        const uint8_t* src = g_o[epoch & 1][b * 8] + hf * 8192;
#pragma unroll
        for (int c = 0; c < 8; c++) bulk_g2s(sb + SM_O + c * 8192, src + c * 16384, 8192, bar(B_FULLA + 4 + (c >> 2)));
        PROF(23);
        int sl = 0;
#pragma unroll 1
        for (int n = 0; n < 16; n++) {
          mbar_wait(bar(B_EMPTYC + sl), (0x8E38u >> n) & 1);
          const uint32_t d = sb + cslot(sl), fb = bar(B_FULLC + sl);
          if (n < 9 && n != 0) {
            const int k0 = ((kb0 + n - 1) & 7) * 64;
            mbar_expect(fb, 24576);
            tma3d(d, &p.tm_g2, j * 224 + 128, k0, 0, fb);
            tma3d(d + 12288, &p.tm_u2, j * 224 + 128, k0, 0, fb);
          } else {
            const int k0 = ((kb0 + 2 * n) & 7) * 64, c0 = j * 224 + (n >= 12 ? 64 : 0);
            mbar_expect(fb, 32768);
            tma2d(d, &p.tm_g1, c0, k0, fb);
            tma2d(d + 16384, &p.tm_u1, c0, k0, fb);
          }
          sl = (sl == 2) ? 0 : sl + 1;
        }
#pragma unroll 1
        for (int u = 0; u < 8; u++) {
          const uint32_t d = sb + ((0x51643025u >> (4 * u)) & 15) * 32768;
          const uint32_t fb = bar(8 + ((0x1001000f03110210ull >> (8 * u)) & 255));
          mbar_wait(bar(14 + ((0xD10C3E2Du >> (4 * u)) & 15)), (0x65u >> u) & 1);
          mbar_expect(fb, 28672);
          tma2d(d, &p.tm_d, hf * 256 + ((pi + 1 + (u >> 1)) & 3) * 64, (j ^ (u & 1)) * 224, fb);
        }
      }
    } else {
      const int hw = warp - 9;
      nb_sync(0, 384);
      asm volatile("barrier.cluster.arrive.relaxed.aligned;" ::: "memory");
      nb_sync(NB_RELKV, 256 + 96);
      const unsigned epoch = lds32(sb + SM_EPOCH);
      if (opaque(hw == 0)) {
        if (lane == 0) red_release(&g_flag[cta][0]);
        mbar_wait(bar(B_WO), 0);
        {
          const uint4 zv = make_uint4(0u, 0u, 0u, 0u);
          uint8_t* d1 = g_o[(epoch & 1) ^ 1][cta] + lane * 16;
          uint8_t* d2 = g_p[(epoch & 1) ^ 1][cta][0] + lane * 16;
#pragma unroll 1
          for (int i = 0; i < 32; i++) {
            stg128(d1 + i * 512, zv); stg128(d2 + i * 512, zv); stg128(d2 + 16384 + i * 512, zv); stg128(d2 + 32768 + i * 512, zv);
          }
          stg128((uint8_t*)g_stat2[(epoch & 1) ^ 1][cta] + lane * 16, zv);
          stg128((uint8_t*)g_stat2[(epoch & 1) ^ 1][cta] + 512 + lane * 16, zv);
        }
        nb_sync(NB_RELH, 256 + 32);
        if (lane == 0) red_release(&g_flag[cta][2]);
        __syncwarp();
        if (lane < 8) poll_flag(&g_flag[b * 8 + lane][2], epoch + 1);
        __syncwarp();
        if (lane == 0) {
          fence_async_global();
#pragma unroll
          for (int m = 1; m < 4; m++) {
            mbar_expect(bar(B_FULLA + m), 32768);
            bulk_g2s_pair(sb + aslot(m) + hf * 16384, g_h[b * 8 + ((kb0 + 2 * m) & 7) + hf], 16384, bar(B_FULLA + m));
          }
          PROF(22);
        }
        fence_acq();
        __syncwarp();
        if (lane == 0) { mbar_wait(bar(B_RECV), 0); mbar_expect(bar(B_RECV), 40960); mbar_expect(bar(B_WO), 16384); mbar_arrive(bar(B_AUX)); }
      } else {
        const int h2 = hw - 1;
        if (lane < 28) {
          const __nv_bfloat16* src = (h2 == 0 ? p.wg : p.wu) + (size_t)(32 * b) * FF + j * 224 + lane * 8;
          float s[8] = {0.f, 0.f, 0.f, 0.f, 0.f, 0.f, 0.f, 0.f};
#pragma unroll 1
          for (int r0 = 0; r0 < 32; r0 += 4) {
            uint4 v[4];
#pragma unroll
            for (int r = 0; r < 4; r++) v[r] = ldg128_nc(src + (size_t)(r0 + r) * FF);
#pragma unroll
            for (int r = 0; r < 4; r++) acc8(s, v[r]);
          }
          float2* d = (float2*)&g_cs2[b][j][lane * 16 + h2 * 2];
#pragma unroll
          for (int e = 0; e < 4; e++) d[2 * e] = make_float2(s[2 * e], s[2 * e + 1]);
        }
        __syncwarp();
        if (lane == 0) { red_release(&g_gflag[j][0]); poll_flag(&g_gflag[j][0], 32 * (epoch + 1)); fence_acq(); }
        __syncwarp();
#pragma unroll 1
        for (int c = h2 * 32 + lane; c < 112; c += 64) {
          float4 a = make_float4(0.f, 0.f, 0.f, 0.f);
#pragma unroll 4
          for (int bb = 0; bb < 16; bb++) {
            float4 t = ldg128f_cg(&g_cs2[bb][j][c * 4]);
            a.x += t.x; a.y += t.y; a.z += t.z; a.w += t.w;
          }
          sts128f(sb + SM_CS + c * 16, a);
        }
        __syncwarp();
        if (lane == 0) { mbar_arrive(bar(B_AUX)); PROF(24); }
      }
    }
    __syncwarp();
    asm volatile("barrier.cluster.wait.acquire.aligned;" ::: "memory");
  } else {
    asm volatile("setmaxnreg.inc.sync.aligned.u32 232;");
    const int wg = warp >> 2, g = lane >> 2, q4 = lane & 3;
    const uint32_t peer = (uint32_t)(hf ^ 1);
    const uint32_t ONES = 0x3f803f80u;
    const int tile = wg ? 11 - warp : warp;
    nb_sync(0, 384);
    asm volatile("barrier.cluster.arrive.relaxed.aligned;" ::: "memory");
    uint32_t qf[4][4];
    {
      uint32_t xa[32][4];
      float rs0, rs1;
      float accX[32], accY[32];
      {
        float sa[2][4] = {}, va[2][4] = {}, vb[2][4] = {};
        const uint32_t xrow = sb + SM_X + (tile * 16 + (lane & 15)) * 128;
        const uint32_t yrow = sb + SM_X + (tile * 16 + (lane & 7) + (lane >> 4) * 8) * 128;
#pragma unroll
        for (int k8 = 0; k8 < 32; k8 += 8) {
          mbar_wait(bar(B_FULLA + (k8 >> 3)), 0);
          if (k8 == 0) PROFT(0, 19);
          if (k8 == 24) PROFT(0, 26);
          uint32_t y[8][4];
#pragma unroll
          for (int k = k8; k < k8 + 8; k++) {
            ldsm4(xrow + (k >> 2) * 16384 + ((((k & 3) * 2 + (lane >> 4)) ^ (lane & 7)) << 4), xa[k][0], xa[k][1], xa[k][2], xa[k][3]);
            ldsm4(yrow + (k >> 2) * 16384 + ((((k & 3) * 2 + ((lane >> 3) & 1)) ^ (lane & 7)) << 4), y[k & 7][0], y[k & 7][1], y[k & 7][2], y[k & 7][3]);
          }
          if (k8 == 24) { __syncwarp(); if (lane == 0) mbar_arrive(bar(B_CDONE)); }
#pragma unroll
          for (int k = k8; k < k8 + 8; k++) {
            mma_acc(sa[k & 1], xa[k][0], xa[k][1], xa[k][2], xa[k][3], ONES, ONES);
            mma_acc(va[k & 1], xa[k][0], xa[k][1], xa[k][2], xa[k][3], y[k & 7][0], y[k & 7][1]);
            mma_acc(vb[k & 1], xa[k][0], xa[k][1], xa[k][2], xa[k][3], y[k & 7][2], y[k & 7][3]);
          }
        }
        const float mean0 = (sa[0][0] + sa[1][0]) * (1.f / DM), mean1 = (sa[0][2] + sa[1][2]) * (1.f / DM);
        const uint32_t h0 = pack_bf16(mean0, mean0), h1 = pack_bf16(mean1, mean1);
        const float e0 = __shfl_sync(0xffffffffu, (g & 1) ? va[0][1] + va[1][1] : va[0][0] + va[1][0], (lane & 28) + (g >> 1));
        const float e1 = __shfl_sync(0xffffffffu, (g & 1) ? vb[0][3] + vb[1][3] : vb[0][2] + vb[1][2], (lane & 28) + (g >> 1));
        rs0 = rsqrtf(fmaxf(e0 * (1.f / DM) - mean0 * mean0, 0.f) + LN_EPS);
        rs1 = rsqrtf(fmaxf(e1 * (1.f / DM) - mean1 * mean1, 0.f) + LN_EPS);
        PROFT(0, 1);
        const uint64_t db = mkdesc(sb + SM_WK, 8192, 1024, 1);
#pragma unroll
        for (int kb = 0; kb < 8; kb++) {
#pragma unroll
          for (int k = 4 * kb; k < 4 * kb + 4; k++) {
            xa[k][0] = bsub2(xa[k][0], h0); xa[k][1] = bsub2(xa[k][1], h1); xa[k][2] = bsub2(xa[k][2], h0); xa[k][3] = bsub2(xa[k][3], h1);
          }
          if ((kb & 3) == 0) mbar_wait(bar(B_FULLW + (kb >> 2)), 0);
          wg_fence();
#pragma unroll
          for (int k = 4 * kb; k < 4 * kb + 4; k++) wgmma_rs_n64(accX, xa[k][0], xa[k][1], xa[k][2], xa[k][3], db + k * 128, k != 0);
        }
        wg_commit();
      }
      NEW_PHASE();
      uint8_t* gkv = g_kv[cta] + tile * 4096 + lane * 4;
      const uint32_t skv = sb + SM_KV + 65536 + tile * 4096 + lane * 4;
#pragma unroll
      for (int ps = 0; ps < 2; ps++) {
        const uint64_t db = mkdesc(sb + (ps == 0 ? SM_WV : SM_WQ), 8192, 1024, 1);
#pragma unroll
        for (int kb = 0; kb < 8; kb++) {
          if ((kb & 3) == 0) mbar_wait(bar(B_FULLW + 2 + ps * 2 + (kb >> 2)), 0);
          if (kb <= 2 || kb == 4) wg_fence();
#pragma unroll
          for (int k = 4 * kb; k < 4 * kb + 4; k++) {
            if (ps == 0) wgmma_rs_n64(accY, xa[k][0], xa[k][1], xa[k][2], xa[k][3], db + k * 128, k != 0);
            else wgmma_rs_n64(accX, xa[k][0], xa[k][1], xa[k][2], xa[k][3], db + k * 128, k != 0);
          }
          if (kb == 0) {
            wg_commit();
            wg_wait<1>();
            if (ps == 0) { pin(accX); if (lane == 0) mbar_arrive(bar(B_CDONE)); PROFT(0, 2); } else { pin(accY); PROFT(0, 3); }
          }
          if (kb < 2) {
            const float* a = (ps == 0) ? accX : accY;
#pragma unroll
            for (int i = 4 * kb; i < 4 * kb + 4; i++) {
              const uint32_t lo = pack_bf16(rs0 * a[4 * i], rs0 * a[4 * i + 1]), hi = pack_bf16(rs1 * a[4 * i + 2], rs1 * a[4 * i + 3]);
              stg32(gkv + (ps * 8 + i) * 128, lo); stg32(gkv + 2048 + (ps * 8 + i) * 128, hi);
              sts32(skv + (ps * 8 + i) * 128, lo); sts32(skv + 2048 + (ps * 8 + i) * 128, hi);
            }
            if (ps == 1 && kb == 1) nb_arrive(NB_RELKV, 256 + 96);
          }
        }
        wg_commit();
      }
      wg_wait<0>();
      pin(accX);
      if (lane == 0) mbar_arrive(bar(B_CDONE));
      nb_sync(NB_CONS, 256);
      const float QS = 0.25f * 1.4426950408889634f;
      const float r0 = rs0 * QS, r1 = rs1 * QS;
#pragma unroll
      for (int i = 0; i < 8; i++) {
        qf[i >> 1][(i & 1) * 2] = pack_bf16(r0 * accX[4 * i], r0 * accX[4 * i + 1]);
        qf[i >> 1][(i & 1) * 2 + 1] = pack_bf16(r1 * accX[4 * i + 2], r1 * accX[4 * i + 3]);
      }
    }
    NEW_PHASE();
    PROFT(0, 5);
    const unsigned par = lds32(sb + SM_EPOCH) & 1;
    const int prow = hf * 64 + (warp & 3) * 16;
    uint32_t xres[16];
    {
      const __nv_bfloat16* xs = p.x + (size_t)(b * 128 + prow + g) * DM + (kb0 + wg) * 64 + q4 * 2;
#pragma unroll
      for (int i = 0; i < 8; i++) { xres[2 * i] = ldg32_nc(xs + i * 8); xres[2 * i + 1] = ldg32_nc(xs + 8 * DM + i * 8); }
    }
    attention(sb, qf, b, tile, lane, g_o[par][cta] + tile * 2048 + lane * 16);
    __syncwarp();
    if (lane == 0) { red_relaxed(&g_flag[cta][1]); mbar_arrive(bar(B_CDONE)); }
    NEW_PHASE();
    PROFT(0, 6);
    PROFT(128, 30);
    asm volatile("barrier.cluster.wait.acquire.aligned;" ::: "memory");
    if (lane == 0) mbar_arrive_remote(mapa(bar(B_PEER), peer));
    {
      float acc[32];
      uint4 ov[2][16];
      mbar_wait(bar(B_WO), 0);
      const uint32_t so = sb + SM_O + (warp & 3) * 2048 + lane * 16;
      const uint64_t dwo = mkdesc(sb + SM_WO + wg * 65536, 8192, 1024, 1);
#pragma unroll
      for (int i = 0; i < 2; i++) {
        mbar_wait(bar(B_FULLA + 4 + i), 0);
        if (i == 0) PROFT(0, 7);
#pragma unroll
        for (int k = 0; k < 16; k++) ov[i][k] = lds128(so + i * 32768 + (k >> 2) * 8192 + (k & 3) * 512);
        for (int it = 0; __builtin_expect(min_word<16>(ov[i]) == 0, 0) && it < (1 << 17); it++) {
          const uint8_t* src = g_o[par][b * 8 + i * 4] + (hf * 4 + (warp & 3)) * 2048 + lane * 16;
#pragma unroll
          for (int k = 0; k < 16; k++) ov[i][k] = ldg128_ll(src + (k >> 2) * 16384 + (k & 3) * 512);
        }
        __syncwarp();
        if (lane == 0) mbar_arrive(bar(B_EMPTYC + i));
        wg_fence();
#pragma unroll
        for (int k = (i == 0 ? 0 : -5); k < (i == 0 ? 11 : 16); k++) {
          const int x = i * 16 + k;
          wgmma_rs_n64(acc, ov[x >> 4][x & 15].x, ov[x >> 4][x & 15].y, ov[x >> 4][x & 15].z, ov[x >> 4][x & 15].w,
                       dwo + x * 128, x != 0);
        }
        wg_commit();
      }
      mbar_wait(bar(B_PEER), 0);
      wg_wait<0>();
      pin(acc);
      if (lane == 0) mbar_arrive(bar(B_EMPTYC + 2));
      PROFT(0, 8);
      const uint32_t hoff = wg * 16384 + prow * 128 + lane * 4;
      uint8_t* gh = g_h[b * 8 + kb0] + hoff;
      const uint32_t sh = sb + SM_HE + hoff;
#pragma unroll
      for (int i = 0; i < 8; i++) {
        xres[2 * i] = pack_bf16(acc[4 * i] + bf_lo(xres[2 * i]), acc[4 * i + 1] + bf_hi(xres[2 * i]));
        xres[2 * i + 1] = pack_bf16(acc[4 * i + 2] + bf_lo(xres[2 * i + 1]), acc[4 * i + 3] + bf_hi(xres[2 * i + 1]));
        stg32(gh + i * 128, xres[2 * i]); stg32(gh + 1024 + i * 128, xres[2 * i + 1]);
        sts32(sh + i * 128, xres[2 * i]); sts32(sh + 1024 + i * 128, xres[2 * i + 1]);
      }
      nb_arrive(NB_RELH, 256 + 32);
      fence_async_smem();
      __syncwarp();
      if (lane == 0) bulk_s2peer(mapa(sh, peer), sh, 2048, mapa(bar(B_RECV), peer));
      PROFT(0, 18);
      float sm[4] = {0.f, 0.f, 0.f, 0.f}, sq[4] = {0.f, 0.f, 0.f, 0.f};
#pragma unroll
      for (int k = 0; k < 4; k++) mma_acc(sm, xres[4 * k], xres[4 * k + 1], xres[4 * k + 2], xres[4 * k + 3], ONES, ONES);
      const float s0 = sm[0] * (1.f / 64), s1 = sm[2] * (1.f / 64);
      const uint32_t c0 = pack_bf16(s0, s0), c1 = pack_bf16(s1, s1);
#pragma unroll
      for (int k = 0; k < 4; k++) {
        const uint32_t a0 = bsub2(xres[4 * k], c0), a1 = bsub2(xres[4 * k + 1], c1), a2 = bsub2(xres[4 * k + 2], c0), a3 = bsub2(xres[4 * k + 3], c1);
        mma_acc(sq, bmul2(a0, a0), bmul2(a1, a1), bmul2(a2, a2), bmul2(a3, a3), ONES, ONES);
      }
      const float e0 = s0 - bf_lo(c0), e1 = s1 - bf_lo(c1);
      if (q4 == 0)
        stg128_ll(&g_stat2[par][b * 8 + kb0 + wg][(prow >> 1) + g], __float_as_uint(s0), __float_as_uint(sq[0] - 64.f * e0 * e0), __float_as_uint(s1),
                  __float_as_uint(sq[2] - 64.f * e1 * e1));
      PROFT(0, 21);
      nb_sync(NB_CONS, 256);
      mbar_wait(bar(B_RECV), 0);
    }
    NEW_PHASE();
    PROFT(0, 9);
    uint32_t own[56];
    float2 st0, st1;
    const uint32_t csb = sb + SM_CS + q4 * 16;
    float accC[96], accA[64];
    float (&accB)[64] = *reinterpret_cast<float (*)[64]>(&accC[0]);
    {
      {
        const uint64_t da = mkdesc(sb + aslot(0) + wg * 8192, 128, 1024, 0);
        const uint64_t db = mkdesc(sb + cslot(0), 16384, 1024, 1), dc = mkdesc(sb + cslot(1), 4096, 512, 2);
        mbar_wait(bar(B_FULLC), 0);
        wg_fence();
#pragma unroll
        for (int k = 0; k < 8; k++) wgmma_ss_n128(accA, da + (k >> 2) * 1024 + (k & 3) * 16, db + k * 128, k != 0);
        wg_commit();
        mbar_wait(bar(B_FULLC + 1), 0);
        wg_fence();
#pragma unroll
        for (int k = 0; k < 4; k++) wgmma_ss_n192(accC, da + k * 16, dc + k * 64, k != 0);
        wg_commit();
        wg_wait<1>();
        pin(accA);
        if (lane == 0) mbar_arrive(bar(B_EMPTYC));
      }
      const uint4* sp = &g_stat2[par][b * 8 + q4 * 2][warp * 8 + g];
      uint4 t0 = make_uint4(0u, 0u, 0u, 0u), t1 = t0;
      PROFT(0, 31);
      int sl = 2;
#pragma unroll 1
      for (int kp = 1; kp < 8; kp++) {
        if ((kp & 1) == 0) mbar_wait(bar(B_FULLA + (kp >> 1)), 1);
        mbar_wait(bar(B_FULLC + sl), (0x1C >> kp) & 1);
        wg_fence();
        const uint64_t da = mkdesc(sb + (kp == 1 ? aslot(0) : 0) + kp * 16384 + wg * 8192, 128, 1024, 0);
        const uint64_t db = mkdesc(sb + cslot(sl), 4096, 512, 2);
#pragma unroll
        for (int k = 0; k < 4; k++) wgmma_ss_n192(accC, da + k * 16, db + k * 64, 1);
        wg_commit();
        if (kp == 5) { t0 = ldg128_ll(sp); t1 = ldg128_ll(sp + 64); }
        wg_wait<1>();
        if (lane == 0) mbar_arrive(bar(B_EMPTYC + (sl == 0 ? 2 : sl - 1)));
        sl = (sl == 2) ? 0 : sl + 1;
      }
#pragma unroll
      for (int n = 9; n < 16; n++) {
        const int m = n & 3;
        NEW_PHASE();
        mbar_wait(bar(B_FULLC + n % 3), (n / 3) & 1);
        const uint64_t da = mkdesc(sb + aslot(m) + wg * 8192, 128, 1024, 0);
        const uint64_t db = mkdesc(sb + cslot(n % 3), 16384, 1024, 1);
#pragma unroll
        for (int k2 = 0; k2 < 4; k2++) {
          wg_fence();
#pragma unroll
          for (int k = 2 * k2; k < 2 * k2 + 2; k++) {
            if (n < 12) wgmma_ss_n128(accA, da + (k >> 2) * 1024 + (k & 3) * 16, db + k * 128, 1);
            else wgmma_ss_n128(accB, da + (k >> 2) * 1024 + (k & 3) * 16, db + k * 128, (m | k) != 0);
          }
          if (k2 == 0 || k2 == 3) wg_commit();
          if (k2 == 0) {
            wg_wait<1>();
            if (lane == 0) {
              mbar_arrive(bar(B_EMPTYC + (n - 1) % 3));
              if (n >= 13) mbar_arrive(bar(B_EMPTYA + n - 13));
              if (n == 14) mbar_arrive_remote(mapa(bar(B_PEER), peer));
            }
            if (n == 9) {
              pin(accC);
              PROFT(0, 11);
              mbar_wait(bar(B_AUX), 0);
      {
        for (int it = 0; min(t0.x, t1.x) == 0 && it < (1 << 17); it++) { t0 = ldg128_ll(sp); t1 = ldg128_ll(sp + 64); }
        __syncwarp();
        float m0 = __uint_as_float(t0.x) + __uint_as_float(t1.x), m1 = __uint_as_float(t0.z) + __uint_as_float(t1.z);
        m0 += __shfl_xor_sync(0xffffffffu, m0, 1); m1 += __shfl_xor_sync(0xffffffffu, m1, 1);
        m0 += __shfl_xor_sync(0xffffffffu, m0, 2); m1 += __shfl_xor_sync(0xffffffffu, m1, 2);
        m0 *= 0.125f; m1 *= 0.125f;
        const float a0 = __uint_as_float(t0.x) - m0, a1 = __uint_as_float(t1.x) - m0, c0 = __uint_as_float(t0.z) - m1, c1 = __uint_as_float(t1.z) - m1;
        float v0 = __uint_as_float(t0.y) + __uint_as_float(t1.y) + 64.f * (a0 * a0 + a1 * a1);
        float v1 = __uint_as_float(t0.w) + __uint_as_float(t1.w) + 64.f * (c0 * c0 + c1 * c1);
        v0 += __shfl_xor_sync(0xffffffffu, v0, 1); v1 += __shfl_xor_sync(0xffffffffu, v1, 1);
        v0 += __shfl_xor_sync(0xffffffffu, v0, 2); v1 += __shfl_xor_sync(0xffffffffu, v1, 2);
        st0 = make_float2(m0, __fdividef(1.f, v0 * (1.f / DM) + LN_EPS));
        st1 = make_float2(m1, __fdividef(1.f, v1 * (1.f / DM) + LN_EPS));
      }
            }
            if (n == 12) { pin(accA); PROFT(0, 12); }
          }
          if (n < 12) {
            const int i = (n - 9) * 4 + k2;
            reglu_block(&accC[4 * i], &accC[48 + 4 * i], csb + (16 + i) * 64, st0.x, st1.x, own[2 * i], own[2 * i + 1]);
          } else if (n < 14) {
            const int i = m * 4 + k2;
            reglu_block(&accA[4 * i], &accA[32 + 4 * i], csb + i * 64, st0.x, st1.x, own[24 + 2 * i], own[25 + 2 * i]);
          } else if ((n == 14 && k2 >= 2) || (n == 15 && k2 < 3)) {
            if (n == 14 && k2 == 2) mbar_wait(bar(B_PEER), 1);
            const uint32_t rb = mapa(sb, peer);
            const int v0 = ((n - 14) * 4 + k2 - 2) * 2;
#pragma unroll
            for (int v = v0; v < v0 + 2; v++)
              st_async128(rb + (v < 6 ? aslot(0) + v * 4096 : aslot(1) + (v - 6) * 4096) + tid * 16, &own[4 * v], rb + SM_BAR + B_RECV * 8);
          }
        }
      }
    }
    NEW_PHASE();
    {
      uint32_t oth[56];
      float (&accP)[32] = *reinterpret_cast<float (*)[32]>(&accA[0]);
      float (&accQ)[32] = *reinterpret_cast<float (*)[32]>(&accC[0]);
      auto krow = [](int v) { return v < 6 ? 128 + v * 16 : (v - 6) * 16; };
      {
        const uint64_t d0 = mkdesc(sb + cslot(1), 8192, 1024, 1), d1 = mkdesc(sb + aslot(2), 8192, 1024, 1);
        const uint32_t rb = mapa(sb, peer);
        mbar_wait(bar(B_FULLC + 1), 1);
#pragma unroll
        for (int c = 0; c < 6; c++) {
          if (c == 2 || c == 4) {
            if (c == 2) mbar_wait(bar(B_RECV), 1);
#pragma unroll
            for (int v = (c == 2 ? 0 : 6); v < (c == 2 ? 6 : 10); v++) {
              const uint4 t = lds128(sb + (v < 6 ? aslot(0) + v * 4096 : aslot(1) + (v - 6) * 4096) + tid * 16);
              oth[4 * v] = t.x; oth[4 * v + 1] = t.y; oth[4 * v + 2] = t.z; oth[4 * v + 3] = t.w;
            }
            if (c == 2) {
              __syncwarp();
              if (lane == 0) mbar_arrive(bar(B_EMPTYA + 0));
              mbar_wait(bar(B_FULLW + 2), 1);
            }
          }
          wg_fence();
#pragma unroll
          for (int e = 0; e < 4; e++) {
            const int x = c * 4 + e;
            if (x < 10) wgmma_rs_n64(accP, own[4 * x], own[4 * x + 1], own[4 * x + 2], own[4 * x + 3], d0 + krow(x) * 8, x != 0);
            else if (x < 20) wgmma_rs_n64(accP, oth[4 * x - 40], oth[4 * x - 39], oth[4 * x - 38], oth[4 * x - 37], d1 + krow(x - 10) * 8, 1);
            else wgmma_rs_n64(accP, own[4 * x - 40], own[4 * x - 39], own[4 * x - 38], own[4 * x - 37], d0 + krow(x - 10) * 8, 1);
          }
          if (c == 0) {
            wg_commit();
            wg_wait<1>();
            pin(accB);
            if (lane == 0) { mbar_arrive(bar(B_EMPTYC + 0)); mbar_arrive(bar(B_EMPTYA + 3)); }
            PROFT(0, 13);
          }
          if (c < 4) {
#pragma unroll
            for (int i = 2 * c; i < 2 * c + 2; i++)
              reglu_block(&accB[4 * i], &accB[32 + 4 * i], csb + (8 + i) * 64, st0.x, st1.x, own[40 + 2 * i], own[41 + 2 * i]);
            st_async128(rb + aslot(1) + 16384 + c * 4096 + tid * 16, &own[40 + 4 * c], rb + SM_BAR + B_WO * 8);
          }
        }
      }
      PROFT(0, 14);
      float sum[32];
      uint32_t hres[16];
      uint4 pt[8];
      const uint8_t* psrc = g_p[par][cta][0] + tid * 16;
#pragma unroll
      for (int s = 1; s < 4; s++) {
        NEW_PHASE();
        const uint32_t w0 = (s == 1) ? cslot(2) : (s == 2 ? cslot(0) : aslot(1)), w1 = (s == 1) ? aslot(3) : (s == 2 ? aslot(0) : cslot(1));
        const uint64_t d0 = mkdesc(sb + w0, 8192, 1024, 1), d1 = mkdesc(sb + w1, 8192, 1024, 1);
        uint8_t* gp = g_p[par][b * 8 + ((pi + s) & 3) * 2 + hf][s - 1] + tid * 16;
        const int cship = (s == 1) ? 3 : 0;
#pragma unroll
        for (int c = 0; c < 7; c++) {
          if (c == 0) {
            if (s == 1) mbar_wait(bar(B_FULLC + 2), 1);
            if (s == 2) mbar_wait(bar(B_FULLC + 0), 0);
            if (s == 3) mbar_wait(bar(B_FULLW + 1), 1);
          }
          if (c == 3) {
            if (s == 1) mbar_wait(bar(B_FULLW + 3), 1);
            if (s == 2) mbar_wait(bar(B_FULLW + 0), 1);
            if (s == 3) mbar_wait(bar(B_FULLC + 1), 0);
          }
          if (c == 0 || c == 3) wg_fence();
#pragma unroll
          for (int e = 0; e < 4; e++) {
            const int x = c * 4 + e;
            if (s & 1) {
              if (x < 14) wgmma_rs_n64(accQ, own[4 * x], own[4 * x + 1], own[4 * x + 2], own[4 * x + 3], d0 + krow(x) * 8, x != 0);
              else wgmma_rs_n64(accQ, oth[4 * x - 56], oth[4 * x - 55], oth[4 * x - 54], oth[4 * x - 53], d1 + krow(x - 14) * 8, 1);
            } else {
              if (x < 14) wgmma_rs_n64(accP, own[4 * x], own[4 * x + 1], own[4 * x + 2], own[4 * x + 3], d0 + krow(x) * 8, x != 0);
              else wgmma_rs_n64(accP, oth[4 * x - 56], oth[4 * x - 55], oth[4 * x - 54], oth[4 * x - 53], d1 + krow(x - 14) * 8, 1);
            }
          }
          if (s == 1 && c == 2) {
            mbar_wait(bar(B_WO), 1);
#pragma unroll
            for (int v = 10; v < 14; v++) {
              const uint4 t = lds128(sb + aslot(1) + (v - 6) * 4096 + tid * 16);
              oth[4 * v] = t.x; oth[4 * v + 1] = t.y; oth[4 * v + 2] = t.z; oth[4 * v + 3] = t.w;
            }
            __syncwarp();
            if (lane == 0) mbar_arrive(bar(B_EMPTYA + 1));
            const uint64_t dz = mkdesc(sb + aslot(2), 8192, 1024, 1);
            wg_fence();
#pragma unroll
            for (int v = 10; v < 14; v++) wgmma_rs_n64(accP, oth[4 * v], oth[4 * v + 1], oth[4 * v + 2], oth[4 * v + 3], dz + krow(v) * 8, 1);
            wg_commit();
          }
          if (c == cship || c == 6) wg_commit();
          if (c == cship) {
            wg_wait<1>();
            if (s & 1) pin(accP); else pin(accQ);
            if (s == 1 && lane == 0) mbar_arrive(bar(B_EMPTYC + 1));
            const float* a = (s & 1) ? accP : accQ;
#pragma unroll
            for (int i = 0; i < 4; i++)
              stg128_ll(gp + i * 4096, pack_bf16(a[8 * i], a[8 * i + 1]), pack_bf16(a[8 * i + 2], a[8 * i + 3]), pack_bf16(a[8 * i + 4], a[8 * i + 5]),
                        pack_bf16(a[8 * i + 6], a[8 * i + 7]));
            PROFT(0, 26 + s);
          }
          if (s == 3 && c == 0) {
#pragma unroll
            for (int i = 0; i < 8; i++) pt[i] = ldg128_ll(psrc + i * 4096);
          }
          if (s == 3 && (c == 2 || c == 6)) {
            constexpr int dummy = 0; (void)dummy;
            const int nv = (c == 2) ? 8 : 4, off = (c == 2) ? 0 : 32768;
            if (c == 6) PROFT(0, 15);
            for (int it = 0; __builtin_expect((c == 2 ? min_word<8>(pt) : min_word<4>(pt)) == 0, 0) && it < (1 << 17); it++) {
#pragma unroll
              for (int i = 0; i < nv; i++) pt[i] = ldg128_ll(psrc + off + i * 4096);
            }
#pragma unroll
            for (int i = 0; i < 4; i++) {
              const uint32_t w[4] = {pt[i].x, pt[i].y, pt[i].z, pt[i].w}, u[4] = {pt[4 + i].x, pt[4 + i].y, pt[4 + i].z, pt[4 + i].w};
#pragma unroll
              for (int e = 0; e < 4; e++) {
                if (c == 2) { sum[8 * i + 2 * e] = bf_lo(w[e]) + bf_lo(u[e]); sum[8 * i + 2 * e + 1] = bf_hi(w[e]) + bf_hi(u[e]); }
                else { sum[8 * i + 2 * e] += bf_lo(w[e]); sum[8 * i + 2 * e + 1] += bf_hi(w[e]); }
              }
            }
            __syncwarp();
          }
          if (s == 3 && c == 5) {
#pragma unroll
            for (int i = 0; i < 4; i++) pt[i] = ldg128_ll(psrc + 32768 + i * 4096);
          }
          if (s == 3 && c == 2) {
            const uint8_t* gh = g_h[b * 8 + hf * 4 + pi] + warp * 2048 + lane * 4;
#pragma unroll
            for (int i = 0; i < 8; i++) { hres[2 * i] = ldg32_cg(gh + i * 128); hres[2 * i + 1] = ldg32_cg(gh + 1024 + i * 128); }
          }
        }
      }
      wg_wait<0>();
      pin(accQ);
      PROFT(0, 25);
      __nv_bfloat16* outp = p.out + (size_t)(b * 128 + warp * 16 + g) * DM + hf * 256 + pi * 64 + q4 * 2;
#pragma unroll
      for (int i = 0; i < 8; i++) {
        stg32(outp + i * 8, pack_bf16((accQ[4 * i] + sum[4 * i]) * st0.y + bf_lo(hres[2 * i]), (accQ[4 * i + 1] + sum[4 * i + 1]) * st0.y + bf_hi(hres[2 * i])));
        stg32(outp + 8 * DM + i * 8,
              pack_bf16((accQ[4 * i + 2] + sum[4 * i + 2]) * st1.y + bf_lo(hres[2 * i + 1]), (accQ[4 * i + 3] + sum[4 * i + 3]) * st1.y + bf_hi(hres[2 * i + 1])));
      }
    }
    PROFT(0, 16);
  }
}

typedef CUresult (*EncodeFn)(CUtensorMap*, CUtensorMapDataType, cuuint32_t, void*, const cuuint64_t*, const cuuint64_t*, const cuuint32_t*,
                             const cuuint32_t*, CUtensorMapInterleave, CUtensorMapSwizzle, CUtensorMapL2promotion, CUtensorMapFloatOOBfill);

void make_map(EncodeFn enc, CUtensorMap* m, const void* ptr, int rank, uint64_t d0, uint64_t d1, uint64_t d2, uint64_t s1, uint64_t s2,
              uint32_t b0, uint32_t b1, uint32_t b2, CUtensorMapSwizzle sw) {
  cuuint64_t gd[3] = {d0, d1, d2};
  cuuint64_t gs[2] = {s1, s2};
  cuuint32_t bd[3] = {b0, b1, b2};
  cuuint32_t es[3] = {1, 1, 1};
  enc(m, CU_TENSOR_MAP_DATA_TYPE_BFLOAT16, rank, const_cast<void*>(ptr), gd, gs, bd, es, CU_TENSOR_MAP_INTERLEAVE_NONE, sw,
      CU_TENSOR_MAP_L2_PROMOTION_L2_128B, CU_TENSOR_MAP_FLOAT_OOB_FILL_NONE);
}

}

extern "C" void kernel_launch(void* const* d_in, const int* in_sizes, int n_in, void* d_out, int out_size) {
  (void)in_sizes; (void)n_in; (void)out_size;
  static EncodeFn enc = nullptr;
  if (!enc) {
    void* f = nullptr;
    cudaDriverEntryPointQueryResult qr;
    cudaGetDriverEntryPoint("cuTensorMapEncodeTiled", &f, cudaEnableDefault, &qr);
    enc = (EncodeFn)f;
    cudaFuncSetAttribute(fused_block_kernel, cudaFuncAttributeMaxDynamicSharedMemorySize, SMEM_TOTAL);
  }
  Params p;
  p.x = (const __nv_bfloat16*)d_in[0];
  p.wqkv = (const __nv_bfloat16*)d_in[1];
  p.wo = (const __nv_bfloat16*)d_in[2];
  p.wg = (const __nv_bfloat16*)d_in[4];
  p.wu = (const __nv_bfloat16*)d_in[5];
  p.wd = (const __nv_bfloat16*)d_in[6];
  p.out = (__nv_bfloat16*)d_out;
  make_map(enc, &p.tm_x, p.x, 2, DM, SEQ, 1, DM * 2, 0, 64, 128, 1, CU_TENSOR_MAP_SWIZZLE_128B);
  make_map(enc, &p.tm_qkv, p.wqkv, 2, 1536, 512, 1, 3072, 0, 64, 256, 1, CU_TENSOR_MAP_SWIZZLE_128B);
  make_map(enc, &p.tm_wo, p.wo, 2, 512, 512, 1, 1024, 0, 64, 256, 1, CU_TENSOR_MAP_SWIZZLE_128B);
  make_map(enc, &p.tm_g1, p.wg, 2, FF, 512, 1, FF * 2, 0, 64, 128, 1, CU_TENSOR_MAP_SWIZZLE_128B);
  make_map(enc, &p.tm_u1, p.wu, 2, FF, 512, 1, FF * 2, 0, 64, 128, 1, CU_TENSOR_MAP_SWIZZLE_128B);
  make_map(enc, &p.tm_g2, p.wg, 3, FF, 512, 3, FF * 2, 64, 32, 64, 3, CU_TENSOR_MAP_SWIZZLE_64B);
  make_map(enc, &p.tm_u2, p.wu, 3, FF, 512, 3, FF * 2, 64, 32, 64, 3, CU_TENSOR_MAP_SWIZZLE_64B);
  make_map(enc, &p.tm_d, p.wd, 2, DM, FF, 1, DM * 2, 0, 64, 224, 1, CU_TENSOR_MAP_SWIZZLE_128B);
  fused_block_kernel<<<NCTA, 384, SMEM_TOTAL>>>(p);
}
```

```cpp
#include <cuda_runtime.h>
#include <cuda.h>
#include <cuda_bf16.h>
#include <stdint.h>

namespace {

constexpr int SEQ = 2048, DM = 512, FF = 1792;
constexpr int NCTA = 128;
constexpr float LN_EPS = 1e-5f;

constexpr uint32_t KB = 1024;
constexpr uint32_t SM_X = 0;
constexpr uint32_t SM_WQ = 0, SM_WV = 64 * KB, SM_WK = 128 * KB;
constexpr uint32_t SM_KV = 128 * KB;
__host__ __device__ constexpr uint32_t wopiece(int chunk, int khalf) { return (khalf ? 0u : 64 * KB) + chunk * 32 * KB; }
constexpr uint32_t SM_O = 128 * KB;
constexpr uint32_t SM_HE = 192 * KB;
constexpr uint32_t MISC = 229376;
constexpr uint32_t SM_BAR = MISC;
constexpr uint32_t SM_EPOCH = MISC + 248;
constexpr uint32_t SM_WB = MISC + 640;
constexpr uint32_t SMEM_TOTAL = 232448;
__host__ __device__ constexpr uint32_t cslot(int s) { return 64 * KB + s * 32 * KB; }
__host__ __device__ constexpr uint32_t aslot(int s) { return s < 2 ? 192 * KB - s * 32 * KB : (uint32_t)(s - 2) * 32 * KB; }

__host__ __device__ constexpr uint32_t cstage(int kp) {
  return kp == 2 ? aslot(3) : cslot(0) + (kp & 3) * 24 * KB;
}

constexpr int B_FULLA = 0;
constexpr int B_FULLW = 8;
constexpr int B_EMPTYA = 14;
constexpr int B_KV1 = 18, B_KV2 = 19;
constexpr int B_WO = 20;
constexpr int B_CDONE = 21;
constexpr int B_AUX = 22;
constexpr int B_FULLC = 23;
constexpr int B_EMPTYC = 26;
constexpr int B_RECV = 29;
constexpr int B_PEER = 30;

#define TS0 3
#define HPOS 1
#define NEARLY 3
#define KSP 3
#define VSP 1
constexpr int B_FULLS = 32;
constexpr int B_DONES = 41;
constexpr int B_OHALF = 50, B_ODONE = 51;
constexpr int B_HP = 52, B_HV = 58;
constexpr int NB_CONS = 1, NB_RELKV = 2, NB_WG = 6, NB_RELH = 4, NB_RELS = 5;

__device__ __align__(128) uint8_t g_kv[NCTA][32768];
__device__ __align__(128) uint8_t g_o[NCTA][16384];
__device__ __align__(128) uint8_t g_h[NCTA][16384];
__device__ __align__(128) uint4 g_stat2[NCTA][64];
__device__ __align__(128) uint32_t g_wb[8][64];
__device__ __align__(128) uint2 g_om[NCTA][64];
__device__ __align__(128) uint8_t g_p[NCTA][3][16384];
__device__ unsigned g_flag[NCTA][32];
__device__ unsigned g_ticket[32];
#define CNT(i) do {} while (0)
#define PROF(i) do {} while (0)
#define PROFT(t, i) do {} while (0)

struct Params {
  CUtensorMap tm_x, tm_qkv, tm_wo, tm_g1, tm_u1, tm_g2, tm_u2, tm_d;
  const __nv_bfloat16 *x, *wqkv, *wo, *wg, *wu, *wd;
  __nv_bfloat16* out;
};

__device__ __forceinline__ void mbar_init(uint32_t b, uint32_t c) { asm volatile("mbarrier.init.shared::cta.b64 [%0], %1;" ::"r"(b), "r"(c) : "memory"); }
__device__ __forceinline__ void mbar_expect(uint32_t b, uint32_t bytes) { asm volatile("mbarrier.arrive.expect_tx.shared::cta.b64 _, [%0], %1;" ::"r"(b), "r"(bytes) : "memory"); }
__device__ __forceinline__ void mbar_arrive(uint32_t b) { asm volatile("mbarrier.arrive.shared::cta.b64 _, [%0];" ::"r"(b) : "memory"); }
__device__ __forceinline__ void mbar_arrive_remote(uint32_t rb) { asm volatile("mbarrier.arrive.relaxed.cluster.shared::cluster.b64 _, [%0];" ::"r"(rb) : "memory"); }
__device__ __forceinline__ bool elect_one() {
  uint32_t r;
  asm volatile("{ .reg .pred p; elect.sync _|p, 0xffffffff; selp.u32 %0, 1, 0, p; }" : "=r"(r));
  return r != 0;
}
__device__ __forceinline__ uint32_t mapa(uint32_t a, uint32_t cta) { uint32_t r; asm volatile("mapa.shared::cluster.u32 %0, %1, %2;" : "=r"(r) : "r"(a), "r"(cta)); return r; }
__device__ __forceinline__ void mbar_wait(uint32_t b, uint32_t ph) {
  asm volatile("{ .reg .pred p; .reg .u32 n; mov.u32 n, 0x20000;\n"
               "MW%=: mbarrier.try_wait.parity.shared::cta.b64 p, [%0], %1;\n"
               "@!p add.u32 n, n, -1; @!p setp.eq.u32 p, n, 0; @!p bra MW%=; }" ::"r"(b), "r"(ph) : "memory");
}
__device__ __forceinline__ void tma2d(uint32_t dst, const CUtensorMap* m, int c0, int c1, uint32_t bar) {
  asm volatile("cp.async.bulk.tensor.2d.shared::cluster.global.mbarrier::complete_tx::bytes [%0], [%1, {%3, %4}], [%2];" ::"r"(dst), "l"(m), "r"(bar), "r"(c0), "r"(c1) : "memory");
}
__device__ __forceinline__ void tma2d_pair(uint32_t dst, const CUtensorMap* m, int c0, int c1, uint32_t bar) {
  asm volatile("cp.async.bulk.tensor.2d.shared::cluster.global.mbarrier::complete_tx::bytes.multicast::cluster [%0], [%1, {%3, %4}], [%2], %5;" ::"r"(dst), "l"(m), "r"(bar), "r"(c0), "r"(c1), "h"((uint16_t)3) : "memory");
}
__device__ __forceinline__ void tma3d(uint32_t dst, const CUtensorMap* m, int c0, int c1, int c2, uint32_t bar) {
  asm volatile("cp.async.bulk.tensor.3d.shared::cluster.global.mbarrier::complete_tx::bytes [%0], [%1, {%3, %4, %5}], [%2];" ::"r"(dst), "l"(m), "r"(bar), "r"(c0), "r"(c1), "r"(c2) : "memory");
}
__device__ __forceinline__ void tma5d(uint32_t dst, const CUtensorMap* m, int c0, int c4, uint32_t bar) {
  asm volatile("cp.async.bulk.tensor.5d.shared::cluster.global.mbarrier::complete_tx::bytes [%0], [%1, {%3, %5, %5, %5, %4}], [%2];" ::"r"(dst), "l"(m), "r"(bar), "r"(c0), "r"(c4), "r"(0) : "memory");
}
__device__ __forceinline__ uint32_t bsub2(uint32_t a, uint32_t b) { uint32_t r; asm("sub.rn.bf16x2 %0, %1, %2;" : "=r"(r) : "r"(a), "r"(b)); return r; }
__device__ __forceinline__ uint32_t bmul2(uint32_t a, uint32_t b) { uint32_t r; asm("mul.rn.bf16x2 %0, %1, %2;" : "=r"(r) : "r"(a), "r"(b)); return r; }
__device__ __forceinline__ void bulk_g2s(uint32_t dst, const void* src, uint32_t bytes, uint32_t bar) {
  asm volatile("cp.async.bulk.shared::cluster.global.mbarrier::complete_tx::bytes [%0], [%1], %2, [%3];" ::"r"(dst), "l"(src), "r"(bytes), "r"(bar) : "memory");
}
__device__ __forceinline__ void bulk_g2s_pair(uint32_t dst, const void* src, uint32_t bytes, uint32_t bar) {
  asm volatile("cp.async.bulk.shared::cluster.global.mbarrier::complete_tx::bytes.multicast::cluster [%0], [%1], %2, [%3], %4;" ::"r"(dst), "l"(src), "r"(bytes), "r"(bar), "h"((uint16_t)3) : "memory");
}
__device__ __forceinline__ void bulk_s2g(void* dst, uint32_t src, uint32_t bytes) {
  asm volatile("cp.async.bulk.global.shared::cta.bulk_group [%0], [%1], %2;" ::"l"(dst), "r"(src), "r"(bytes) : "memory");
  asm volatile("cp.async.bulk.commit_group;" ::: "memory");
}
__device__ __forceinline__ void bulk_prefetch(const void* src, uint32_t bytes) { asm volatile("cp.async.bulk.prefetch.L2.global [%0], %1;" ::"l"(src), "r"(bytes) : "memory"); }
__device__ __forceinline__ void prefetch_tm(const CUtensorMap* m) { asm volatile("prefetch.tensormap [%0];" ::"l"(m) : "memory"); }
__device__ __forceinline__ void nb_sync(int id, int n) { asm volatile("bar.sync %0, %1;" ::"r"(id), "r"(n) : "memory"); }
__device__ __forceinline__ void nb_arrive(int id, int n) { asm volatile("bar.arrive %0, %1;" ::"r"(id), "r"(n) : "memory"); }
__device__ __forceinline__ bool nb_any(int id, int n, bool v) {
  uint32_t r;
  asm volatile("{ .reg .pred p, q; setp.ne.u32 p, %1, 0; bar.red.or.pred q, %2, %3, p; selp.u32 %0, 1, 0, q; }" : "=r"(r) : "r"((uint32_t)v), "r"(id), "r"(n) : "memory");
  return r != 0;
}
__device__ __forceinline__ void red_release(unsigned* f) { asm volatile("red.release.gpu.global.add.u32 [%0], 1;" ::"l"(f) : "memory"); }
__device__ __forceinline__ void red_relaxed(unsigned* f) { asm volatile("red.relaxed.gpu.global.add.u32 [%0], 1;" ::"l"(f) : "memory"); }
__device__ __forceinline__ void poll_flag(const unsigned* f, unsigned target) {
  asm volatile("{ .reg .pred p; .reg .u32 n, v; mov.u32 n, 0x20000;\n"
               "PF%=: ld.relaxed.gpu.global.u32 v, [%0]; sub.u32 v, v, %1; setp.ge.s32 p, v, 0;\n"
               "@!p add.u32 n, n, -1; @!p setp.eq.u32 p, n, 0; @!p bra PF%=; }" ::"l"(f), "r"(target) : "memory");
}
__device__ __forceinline__ void fence_async_global() { asm volatile("fence.proxy.async.global;" ::: "memory"); }
__device__ __forceinline__ void acquire_flag(const unsigned* f) { asm volatile("{ .reg .u32 v; ld.acquire.gpu.global.u32 v, [%0]; }" ::"l"(f) : "memory"); }
__device__ __forceinline__ void wg_fence() { asm volatile("wgmma.fence.sync.aligned;" ::: "memory"); }
__device__ __forceinline__ void wg_commit() { asm volatile("wgmma.commit_group.sync.aligned;" ::: "memory"); }
template <int N> __device__ __forceinline__ void wg_wait() { asm volatile("wgmma.wait_group.sync.aligned %0;" ::"n"(N) : "memory"); }
__device__ __forceinline__ uint64_t mkdesc(uint32_t addr, uint32_t lbo, uint32_t sbo, uint64_t sw) {
  return (uint64_t)((addr & 0x3FFFF) >> 4) | ((uint64_t)(lbo >> 4) << 16) | ((uint64_t)(sbo >> 4) << 32) | (sw << 62);
}
__device__ __forceinline__ uint32_t pack_bf16(float lo, float hi) { uint32_t r; asm("cvt.rn.bf16x2.f32 %0, %1, %2;" : "=r"(r) : "f"(hi), "f"(lo)); return r; }
__device__ __forceinline__ uint32_t pack_relu(float lo, float hi) { uint32_t r; asm("cvt.rn.relu.bf16x2.f32 %0, %1, %2;" : "=r"(r) : "f"(hi), "f"(lo)); return r; }
__device__ __forceinline__ float bf_lo(uint32_t v) { return __uint_as_float(v << 16); }
__device__ __forceinline__ float bf_hi(uint32_t v) { return __uint_as_float(v & 0xffff0000u); }
__device__ __forceinline__ float ex2(float x) { float r; asm("ex2.approx.ftz.f32 %0, %1;" : "=f"(r) : "f"(x)); return r; }
__device__ __forceinline__ void sts32(uint32_t a, uint32_t v) { asm volatile("st.shared.u32 [%0], %1;" ::"r"(a), "r"(v) : "memory"); }
__device__ __forceinline__ float2 lds64f(uint32_t a) { float2 v; asm volatile("ld.shared.v2.f32 {%0, %1}, [%2];" : "=f"(v.x), "=f"(v.y) : "r"(a) : "memory"); return v; }
__device__ __forceinline__ void sts64f(uint32_t a, float2 v) { asm volatile("st.shared.v2.f32 [%0], {%1, %2};" ::"r"(a), "f"(v.x), "f"(v.y) : "memory"); }
__device__ __forceinline__ void sts128f(uint32_t a, float4 v) { asm volatile("st.shared.v4.f32 [%0], {%1, %2, %3, %4};" ::"r"(a), "f"(v.x), "f"(v.y), "f"(v.z), "f"(v.w) : "memory"); }
__device__ __forceinline__ float4 lds128f(uint32_t a) { float4 v; asm volatile("ld.shared.v4.f32 {%0, %1, %2, %3}, [%4];" : "=f"(v.x), "=f"(v.y), "=f"(v.z), "=f"(v.w) : "r"(a) : "memory"); return v; }
__device__ __forceinline__ uint4 ldg128_nc(const void* p) { uint4 v; asm volatile("ld.global.nc.v4.u32 {%0, %1, %2, %3}, [%4];" : "=r"(v.x), "=r"(v.y), "=r"(v.z), "=r"(v.w) : "l"(p)); return v; }
__device__ __forceinline__ uint32_t ldg32_nc(const void* p) { uint32_t v; asm volatile("ld.global.nc.u32 %0, [%1];" : "=r"(v) : "l"(p)); return v; }
__device__ __forceinline__ uint32_t ldg32_cg(const void* p) { uint32_t v; asm volatile("ld.global.cg.u32 %0, [%1];" : "=r"(v) : "l"(p) : "memory"); return v; }
__device__ __forceinline__ float4 ldg128f_cg(const void* p) { float4 v; asm volatile("ld.global.cg.v4.f32 {%0, %1, %2, %3}, [%4];" : "=f"(v.x), "=f"(v.y), "=f"(v.z), "=f"(v.w) : "l"(p) : "memory"); return v; }
__device__ __forceinline__ float2 ldg64f_cg(const void* p) { float2 v; asm volatile("ld.global.cg.v2.f32 {%0, %1}, [%2];" : "=f"(v.x), "=f"(v.y) : "l"(p) : "memory"); return v; }
__device__ __forceinline__ void stg32(void* p, uint32_t v) { asm volatile("st.global.u32 [%0], %1;" ::"l"(p), "r"(v) : "memory"); }
__device__ __forceinline__ void stg128_ll(void* p, uint32_t a, uint32_t b, uint32_t c, uint32_t d) {
  asm volatile("st.relaxed.gpu.global.v4.u32 [%0], {%1, %2, %3, %4};" ::"l"(p), "r"(a), "r"(b), "r"(c), "r"(d) : "memory");
}
__device__ __forceinline__ void bulk_s2peer(uint32_t rdst, uint32_t src, uint32_t bytes, uint32_t rbar) {
  asm volatile("cp.async.bulk.shared::cluster.shared::cta.mbarrier::complete_tx::bytes [%0], [%1], %2, [%3];" ::"r"(rdst), "r"(src), "r"(bytes), "r"(rbar) : "memory");
}
__device__ __forceinline__ void stg128(void* p, uint4 v) { asm volatile("st.global.v4.u32 [%0], {%1, %2, %3, %4};" ::"l"(p), "r"(v.x), "r"(v.y), "r"(v.z), "r"(v.w) : "memory"); }
__device__ __forceinline__ void stg64(void* p, uint32_t a, uint32_t b) { asm volatile("st.global.v2.u32 [%0], {%1, %2};" ::"l"(p), "r"(a), "r"(b) : "memory"); }
__device__ __forceinline__ uint4 ldg128_ll(const void* p) {
  uint4 v;
  asm volatile("ld.relaxed.gpu.global.v4.u32 {%0, %1, %2, %3}, [%4];" : "=r"(v.x), "=r"(v.y), "=r"(v.z), "=r"(v.w) : "l"(p) : "memory");
  return v;
}
__device__ __forceinline__ uint2 ldg64_ll(const void* p) { uint2 v; asm volatile("ld.relaxed.gpu.global.v2.u32 {%0, %1}, [%2];" : "=r"(v.x), "=r"(v.y) : "l"(p) : "memory"); return v; }
__device__ __forceinline__ void stg64_ll(void* p, uint32_t a, uint32_t b) { asm volatile("st.relaxed.gpu.global.v2.u32 [%0], {%1, %2};" ::"l"(p), "r"(a), "r"(b) : "memory"); }
__device__ __forceinline__ void sts128(uint32_t a, uint4 v) { asm volatile("st.shared.v4.u32 [%0], {%1, %2, %3, %4};" ::"r"(a), "r"(v.x), "r"(v.y), "r"(v.z), "r"(v.w) : "memory"); }
__device__ __forceinline__ uint32_t lds32(uint32_t a) { uint32_t v; asm volatile("ld.shared.u32 %0, [%1];" : "=r"(v) : "r"(a) : "memory"); return v; }
__device__ __forceinline__ uint4 lds128(uint32_t a) { uint4 v; asm volatile("ld.shared.v4.u32 {%0, %1, %2, %3}, [%4];" : "=r"(v.x), "=r"(v.y), "=r"(v.z), "=r"(v.w) : "r"(a) : "memory"); return v; }
__device__ __forceinline__ void stg128f(void* p, const float* v) { asm volatile("st.global.v4.f32 [%0], {%1, %2, %3, %4};" ::"l"(p), "f"(v[0]), "f"(v[1]), "f"(v[2]), "f"(v[3]) : "memory"); }
__device__ __forceinline__ void st_async128(uint32_t rdst, const uint32_t* v, uint32_t rbar) {
  asm volatile("st.async.weak.shared::cluster.mbarrier::complete_tx::bytes.v4.b32 [%0], {%1, %2, %3, %4}, [%5];" ::"r"(rdst), "r"(v[0]), "r"(v[1]), "r"(v[2]), "r"(v[3]), "r"(rbar) : "memory");
}
__device__ __forceinline__ void fence_async_smem() { asm volatile("fence.proxy.async.shared::cta;" ::: "memory"); }
__device__ __forceinline__ uint32_t tagw(uint32_t v, uint32_t t, uint32_t m) { uint32_t r; asm("lop3.b32 %0, %1, %2, %3, 0xD8;" : "=r"(r) : "r"(v), "r"(t), "r"(m)); return r; }
template <int N> __device__ __forceinline__ uint32_t stale(const uint4* v, uint32_t tag) {
  uint32_t m = 0;
#pragma unroll
  for (int i = 0; i < N; i++) m |= v[i].x ^ tag;
  return m & 1;
}
template <int N> __device__ __forceinline__ uint32_t stale_smem(uint32_t addr, uint32_t stride, uint32_t tag) {
  uint32_t w[N], m0 = 0, m1 = 0;
#pragma unroll
  for (int i = 0; i < N; i++) w[i] = lds32(addr + i * stride);
#pragma unroll
  for (int i = 0; i < N; i += 2) { m0 |= w[i] ^ tag; m1 |= w[i + 1] ^ tag; }
  return (m0 | m1) & 1;
}
__device__ __forceinline__ void repair(uint32_t dst, const uint8_t* src, int n, uint32_t dstride, uint32_t sstride, uint32_t tag) {
  const int w = (threadIdx.x >> 3) & 3;
#pragma unroll 1
  for (int i = 0; i < n; i += 4) {
    uint4 v[4];
    uint32_t m;
    int it = 0;
    do {
      m = 0;
#pragma unroll
      for (int k = 0; k < 4; k++) v[k] = ldg128_ll(src + (size_t)(i + k) * sstride);
#pragma unroll
      for (int k = 0; k < 4; k++) m |= (w == 0 ? v[k].x : (w == 1 ? v[k].y : (w == 2 ? v[k].z : v[k].w))) ^ tag;
    } while ((m & 1) && ++it < (1 << 17));
#pragma unroll
    for (int k = 0; k < 4; k++) sts128(dst + (i + k) * dstride, v[k]);
  }
  fence_async_smem();
}
template <int N> __device__ __forceinline__ void pin(float (&d)[N]) {
#pragma unroll
  for (int i = 0; i < N; i++) asm volatile("" : "+f"(d[i])::"memory");
}
__device__ __forceinline__ void ldsm4(uint32_t a, uint32_t& r0, uint32_t& r1, uint32_t& r2, uint32_t& r3) {
  asm volatile("ldmatrix.sync.aligned.m8n8.x4.shared.b16 {%0, %1, %2, %3}, [%4];" : "=r"(r0), "=r"(r1), "=r"(r2), "=r"(r3) : "r"(a) : "memory");
}
__device__ __forceinline__ void ldsm4t(uint32_t a, uint32_t& r0, uint32_t& r1, uint32_t& r2, uint32_t& r3) {
  asm volatile("ldmatrix.sync.aligned.m8n8.x4.trans.shared.b16 {%0, %1, %2, %3}, [%4];" : "=r"(r0), "=r"(r1), "=r"(r2), "=r"(r3) : "r"(a) : "memory");
}
__device__ __forceinline__ void mma_acc(float (&c)[4], uint32_t a0, uint32_t a1, uint32_t a2, uint32_t a3, uint32_t b0, uint32_t b1) {
  asm("mma.sync.aligned.m16n8k16.row.col.f32.bf16.bf16.f32 {%0, %1, %2, %3}, {%4, %5, %6, %7}, {%8, %9}, {%0, %1, %2, %3};"
      : "+f"(c[0]), "+f"(c[1]), "+f"(c[2]), "+f"(c[3]) : "r"(a0), "r"(a1), "r"(a2), "r"(a3), "r"(b0), "r"(b1));
}
__device__ __forceinline__ void mma_k8(float (&c)[4], uint32_t a0, uint32_t a1, uint32_t b0) {
  asm("mma.sync.aligned.m16n8k8.row.col.f32.bf16.bf16.f32 {%0, %1, %2, %3}, {%4, %5}, {%6}, {%0, %1, %2, %3};"
      : "+f"(c[0]), "+f"(c[1]), "+f"(c[2]), "+f"(c[3]) : "r"(a0), "r"(a1), "r"(b0));
}
__device__ __forceinline__ void mma_zero(float* d, uint32_t a0, uint32_t a1, uint32_t a2, uint32_t a3, uint32_t b0, uint32_t b1) {
  asm("mma.sync.aligned.m16n8k16.row.col.f32.bf16.bf16.f32 {%0, %1, %2, %3}, {%4, %5, %6, %7}, {%8, %9}, {%10, %10, %10, %10};"
      : "=f"(d[0]), "=f"(d[1]), "=f"(d[2]), "=f"(d[3]) : "r"(a0), "r"(a1), "r"(a2), "r"(a3), "r"(b0), "r"(b1), "f"(0.f));
}

__device__ __forceinline__ void wgmma_rs_n64(float (&d)[32], uint32_t a0, uint32_t a1, uint32_t a2, uint32_t a3, uint64_t db, int sd) {
  asm volatile("{ .reg .pred p; setp.ne.b32 p, %37, 0;\n"
  "wgmma.mma_async.sync.aligned.m64n64k16.f32.bf16.bf16 {%0, %1, %2, %3, %4, %5, %6, %7, %8, %9, %10, %11, %12, %13, %14, %15, %16, %17, %18, %19, %20, %21, %22, %23, %24, %25, %26, %27, %28, %29, %30, %31}, {%32, %33, %34, %35}, %36, p, 1, 1, 1;\n}"
  : "+f"(d[0]), "+f"(d[1]), "+f"(d[2]), "+f"(d[3]), "+f"(d[4]), "+f"(d[5]), "+f"(d[6]), "+f"(d[7]), "+f"(d[8]), "+f"(d[9]), "+f"(d[10]), "+f"(d[11]), "+f"(d[12]), "+f"(d[13]), "+f"(d[14]), "+f"(d[15]), "+f"(d[16]), "+f"(d[17]), "+f"(d[18]), "+f"(d[19]), "+f"(d[20]), "+f"(d[21]), "+f"(d[22]), "+f"(d[23]), "+f"(d[24]), "+f"(d[25]), "+f"(d[26]), "+f"(d[27]), "+f"(d[28]), "+f"(d[29]), "+f"(d[30]), "+f"(d[31]) : "r"(a0), "r"(a1), "r"(a2), "r"(a3), "l"(db), "r"(sd));
}
__device__ __forceinline__ void wgmma_ss_n64(float (&d)[32], uint64_t da, uint64_t db, int sd) {
  asm volatile("{ .reg .pred p; setp.ne.b32 p, %34, 0;\n"
  "wgmma.mma_async.sync.aligned.m64n64k16.f32.bf16.bf16 {%0, %1, %2, %3, %4, %5, %6, %7, %8, %9, %10, %11, %12, %13, %14, %15, %16, %17, %18, %19, %20, %21, %22, %23, %24, %25, %26, %27, %28, %29, %30, %31}, %32, %33, p, 1, 1, 0, 1;\n}"
  : "+f"(d[0]), "+f"(d[1]), "+f"(d[2]), "+f"(d[3]), "+f"(d[4]), "+f"(d[5]), "+f"(d[6]), "+f"(d[7]), "+f"(d[8]), "+f"(d[9]), "+f"(d[10]), "+f"(d[11]), "+f"(d[12]), "+f"(d[13]), "+f"(d[14]), "+f"(d[15]), "+f"(d[16]), "+f"(d[17]), "+f"(d[18]), "+f"(d[19]), "+f"(d[20]), "+f"(d[21]), "+f"(d[22]), "+f"(d[23]), "+f"(d[24]), "+f"(d[25]), "+f"(d[26]), "+f"(d[27]), "+f"(d[28]), "+f"(d[29]), "+f"(d[30]), "+f"(d[31]) : "l"(da), "l"(db), "r"(sd));
}
__device__ __forceinline__ void wgmma_ss_n128(float (&d)[64], uint64_t da, uint64_t db, int sd) {
  asm volatile("{ .reg .pred p; setp.ne.b32 p, %66, 0;\n"
  "wgmma.mma_async.sync.aligned.m64n128k16.f32.bf16.bf16 {%0, %1, %2, %3, %4, %5, %6, %7, %8, %9, %10, %11, %12, %13, %14, %15, %16, %17, %18, %19, %20, %21, %22, %23, %24, %25, %26, %27, %28, %29, %30, %31, %32, %33, %34, %35, %36, %37, %38, %39, %40, %41, %42, %43, %44, %45, %46, %47, %48, %49, %50, %51, %52, %53, %54, %55, %56, %57, %58, %59, %60, %61, %62, %63}, %64, %65, p, 1, 1, 0, 1;\n}"
  : "+f"(d[0]), "+f"(d[1]), "+f"(d[2]), "+f"(d[3]), "+f"(d[4]), "+f"(d[5]), "+f"(d[6]), "+f"(d[7]), "+f"(d[8]), "+f"(d[9]), "+f"(d[10]), "+f"(d[11]), "+f"(d[12]), "+f"(d[13]), "+f"(d[14]), "+f"(d[15]), "+f"(d[16]), "+f"(d[17]), "+f"(d[18]), "+f"(d[19]), "+f"(d[20]), "+f"(d[21]), "+f"(d[22]), "+f"(d[23]), "+f"(d[24]), "+f"(d[25]), "+f"(d[26]), "+f"(d[27]), "+f"(d[28]), "+f"(d[29]), "+f"(d[30]), "+f"(d[31]), "+f"(d[32]), "+f"(d[33]), "+f"(d[34]), "+f"(d[35]), "+f"(d[36]), "+f"(d[37]), "+f"(d[38]), "+f"(d[39]), "+f"(d[40]), "+f"(d[41]), "+f"(d[42]), "+f"(d[43]), "+f"(d[44]), "+f"(d[45]), "+f"(d[46]), "+f"(d[47]), "+f"(d[48]), "+f"(d[49]), "+f"(d[50]), "+f"(d[51]), "+f"(d[52]), "+f"(d[53]), "+f"(d[54]), "+f"(d[55]), "+f"(d[56]), "+f"(d[57]), "+f"(d[58]), "+f"(d[59]), "+f"(d[60]), "+f"(d[61]), "+f"(d[62]), "+f"(d[63]) : "l"(da), "l"(db), "r"(sd));
}
__device__ __forceinline__ void wgmma_ss_n192(float (&d)[96], uint64_t da, uint64_t db, int sd) {
  asm volatile("{ .reg .pred p; setp.ne.b32 p, %98, 0;\n"
  "wgmma.mma_async.sync.aligned.m64n192k16.f32.bf16.bf16 {%0, %1, %2, %3, %4, %5, %6, %7, %8, %9, %10, %11, %12, %13, %14, %15, %16, %17, %18, %19, %20, %21, %22, %23, %24, %25, %26, %27, %28, %29, %30, %31, %32, %33, %34, %35, %36, %37, %38, %39, %40, %41, %42, %43, %44, %45, %46, %47, %48, %49, %50, %51, %52, %53, %54, %55, %56, %57, %58, %59, %60, %61, %62, %63, %64, %65, %66, %67, %68, %69, %70, %71, %72, %73, %74, %75, %76, %77, %78, %79, %80, %81, %82, %83, %84, %85, %86, %87, %88, %89, %90, %91, %92, %93, %94, %95}, %96, %97, p, 1, 1, 0, 1;\n}"
  : "+f"(d[0]), "+f"(d[1]), "+f"(d[2]), "+f"(d[3]), "+f"(d[4]), "+f"(d[5]), "+f"(d[6]), "+f"(d[7]), "+f"(d[8]), "+f"(d[9]), "+f"(d[10]), "+f"(d[11]), "+f"(d[12]), "+f"(d[13]), "+f"(d[14]), "+f"(d[15]), "+f"(d[16]), "+f"(d[17]), "+f"(d[18]), "+f"(d[19]), "+f"(d[20]), "+f"(d[21]), "+f"(d[22]), "+f"(d[23]), "+f"(d[24]), "+f"(d[25]), "+f"(d[26]), "+f"(d[27]), "+f"(d[28]), "+f"(d[29]), "+f"(d[30]), "+f"(d[31]), "+f"(d[32]), "+f"(d[33]), "+f"(d[34]), "+f"(d[35]), "+f"(d[36]), "+f"(d[37]), "+f"(d[38]), "+f"(d[39]), "+f"(d[40]), "+f"(d[41]), "+f"(d[42]), "+f"(d[43]), "+f"(d[44]), "+f"(d[45]), "+f"(d[46]), "+f"(d[47]), "+f"(d[48]), "+f"(d[49]), "+f"(d[50]), "+f"(d[51]), "+f"(d[52]), "+f"(d[53]), "+f"(d[54]), "+f"(d[55]), "+f"(d[56]), "+f"(d[57]), "+f"(d[58]), "+f"(d[59]), "+f"(d[60]), "+f"(d[61]), "+f"(d[62]), "+f"(d[63]), "+f"(d[64]), "+f"(d[65]), "+f"(d[66]), "+f"(d[67]), "+f"(d[68]), "+f"(d[69]), "+f"(d[70]), "+f"(d[71]), "+f"(d[72]), "+f"(d[73]), "+f"(d[74]), "+f"(d[75]), "+f"(d[76]), "+f"(d[77]), "+f"(d[78]), "+f"(d[79]), "+f"(d[80]), "+f"(d[81]), "+f"(d[82]), "+f"(d[83]), "+f"(d[84]), "+f"(d[85]), "+f"(d[86]), "+f"(d[87]), "+f"(d[88]), "+f"(d[89]), "+f"(d[90]), "+f"(d[91]), "+f"(d[92]), "+f"(d[93]), "+f"(d[94]), "+f"(d[95]) : "l"(da), "l"(db), "r"(sd));
}

__device__ __forceinline__ void mma_c4(float* d, const uint32_t (&q)[4], uint32_t b0, uint32_t b1, const float (&c)[4]) {
  asm("mma.sync.aligned.m16n8k16.row.col.f32.bf16.bf16.f32 {%0, %1, %2, %3}, {%4, %5, %6, %7}, {%8, %9}, {%10, %11, %12, %13};"
      : "=f"(d[0]), "=f"(d[1]), "=f"(d[2]), "=f"(d[3])
      : "r"(q[0]), "r"(q[1]), "r"(q[2]), "r"(q[3]), "r"(b0), "r"(b1), "f"(c[0]), "f"(c[1]), "f"(c[2]), "f"(c[3]));
}
__device__ __forceinline__ void sblock(float (&s)[8], const uint32_t (&q)[4], uint32_t ka, const float (&c)[4]) {
  uint32_t k0, k1, k2, k3;
  ldsm4(ka, k0, k1, k2, k3);
  mma_c4(&s[0], q, k0, k1, c);
  mma_c4(&s[4], q, k2, k3, c);
}
__device__ __forceinline__ void expack(const float (&s)[8], uint32_t (&p)[4]) {
  p[0] = pack_bf16(ex2(s[0]), ex2(s[1])); p[1] = pack_bf16(ex2(s[2]), ex2(s[3]));
  p[2] = pack_bf16(ex2(s[4]), ex2(s[5])); p[3] = pack_bf16(ex2(s[6]), ex2(s[7]));
}
__device__ __forceinline__ void pvblock(const uint32_t (&p)[4], uint32_t va, float (&o0)[4], float (&o1)[4], float (&l)[4]) {
  const uint32_t ONES = 0x3f803f80u;
  uint32_t v0, v1, v2, v3;
  ldsm4t(va, v0, v1, v2, v3);
  mma_acc(l, p[0], p[1], p[2], p[3], ONES, ONES);
  mma_acc(o0, p[0], p[1], p[2], p[3], v0, v1);
  mma_acc(o1, p[0], p[1], p[2], p[3], v2, v3);
}

__device__ __forceinline__ void attention(uint32_t sb, const uint32_t (&qf)[4][4], int b, int warp  , int lane, uint8_t* go, uint32_t& tag, unsigned* hint, float& pm0, float& pm1) {
  const int g = lane >> 2, q4 = lane & 3, mi = lane >> 3;
  const int tmin = max(0, 16 - 8 * b - warp), tl0 = max(1, tmin);
  const uint32_t kaddr = sb + SM_KV + (2 * warp + (mi >> 1)) * 2048 + (mi & 1) * 128 + (lane & 7) * 16;
  const uint32_t vaddr = sb + SM_KV + (2 * warp + (mi & 1)) * 2048 + (8 + (mi >> 1)) * 128 + (lane & 7) * 16;
  const bool pA = (2 * q4 <= g), pB = (2 * q4 + 1 <= g);
  const uint32_t mk = (pA ? 0x0000ffffu : 0u) | (pB ? 0xffff0000u : 0u);
  const uint32_t ONES = 0x3f803f80u;
  float o0[4][4], o1[4][4], l[4][4], c[4][4];
#pragma unroll
  for (int h = 0; h < 4; h++) {
    float d[4];
    uint32_t k0, k1, k2, k3;
    ldsm4(kaddr + h * 256 + 16 * 4096, k0, k1, k2, k3);
    mma_zero(d, qf[h][0], qf[h][1], qf[h][2], qf[h][3], k0, k1);
    c[h][0] = __shfl_sync(0xffffffffu, -d[0], lane & 28); c[h][2] = __shfl_sync(0xffffffffu, -d[2], lane & 28);
    c[h][1] = __shfl_sync(0xffffffffu, -d[0], 0, 4); c[h][3] = __shfl_sync(0xffffffffu, -d[2], 0, 4);
  }
#pragma unroll 1
  for (int attempt = 0; attempt < 2; attempt++) {
#pragma unroll
    for (int h = 0; h < 4; h++)
#pragma unroll
      for (int e = 0; e < 4; e++) { o0[h][e] = 0.f; o1[h][e] = 0.f; l[h][e] = 0.f; }
    float sc[8], pe[8];
    uint32_t pp[4];
#pragma unroll
    for (int e = 0; e < 8; e++) pe[e] = 0.f;
    if (warp == 0) mbar_wait(sb + SM_BAR + B_KV1 * 8, 0);
    sblock(sc, qf[0], kaddr + 15 * 4096, c[0]);
    uint32_t ka = kaddr + 15 * 4096, va = vaddr + 15 * 4096;
    int t = 15;
#pragma unroll 1
    for (int seg = 0; seg < 3; seg++) {
     if (seg >= 1) mbar_wait(sb + SM_BAR + (B_KV1 - 1 + seg) * 8, 0);
     const int tend = max(tl0, 17 - 8 * seg - warp);
#pragma unroll 1
     for (; t >= tend; t--) {
      float s1[8], s2[8], s3[8];
      uint32_t p[4];
      sblock(s1, qf[1], ka + 256, c[1]);
      pp[0] = pack_bf16(pe[0], pe[1]); pp[1] = pack_bf16(pe[2], pe[3]); pp[2] = pack_bf16(pe[4], pe[5]); pp[3] = pack_bf16(pe[6], pe[7]);
      pvblock(pp, va + 4096 + 768, o0[3], o1[3], l[3]);
      expack(sc, p);
      sblock(s2, qf[2], ka + 512, c[2]);
      pvblock(p, va, o0[0], o1[0], l[0]);
      expack(s1, p);
      sblock(s3, qf[3], ka + 768, c[3]);
      pvblock(p, va + 256, o0[1], o1[1], l[1]);
      expack(s2, p);
      sblock(sc, qf[0], ka - 4096, c[0]);
      pvblock(p, va + 512, o0[2], o1[2], l[2]);
#pragma unroll
      for (int e = 0; e < 8; e++) pe[e] = ex2(s3[e]);
      ka -= 4096; va -= 4096;
     }
    }
    pp[0] = pack_bf16(pe[0], pe[1]); pp[1] = pack_bf16(pe[2], pe[3]); pp[2] = pack_bf16(pe[4], pe[5]); pp[3] = pack_bf16(pe[6], pe[7]);
    pvblock(pp, va + 4096 + 768, o0[3], o1[3], l[3]);
    if (attempt == 0 && lane == 0) mbar_arrive(sb + SM_BAR + B_CDONE * 8);
    tag = __shfl_sync(0xffffffffu, lds32(sb + SM_EPOCH) + 1, 0);
    bool ok = true;
#pragma unroll
    for (int h = 0; h < 4; h++) {
      float d[8], tl[8];
      sblock(d, qf[h], kaddr + h * 256 + 16 * 4096, c[h]);
      sblock(tl, qf[h], kaddr + h * 256, c[h]);
      if (tmin > 0) {
#pragma unroll
        for (int e = 0; e < 8; e++) tl[e] = -INFINITY;
      }
      const uint32_t p0 = pack_bf16(ex2(pA ? d[0] : tl[0]), ex2(pB ? d[1] : tl[1])), p1 = pack_bf16(ex2(d[2]), ex2(d[3]));
      const uint32_t p2 = pack_bf16(ex2(tl[4]), ex2(tl[5])), p3 = pack_bf16(ex2(pA ? d[6] : tl[6]), ex2(pB ? d[7] : tl[7]));
      mma_acc(l[h], p0, p1, p2, p3, ONES, ONES);
      uint32_t v0, v1, v2, v3;
      ldsm4t(vaddr + h * 256 + 16 * 4096, v0, v1, v2, v3);
      mma_acc(o0[h], p0 & mk, p1, 0u, p3 & mk, v0, v1); mma_acc(o1[h], p0 & mk, p1, 0u, p3 & mk, v2, v3);
      ldsm4t(vaddr + h * 256, v0, v1, v2, v3);
      mma_acc(o0[h], p0 & ~mk, 0u, p2, p3 & ~mk, v0, v1); mma_acc(o1[h], p0 & ~mk, 0u, p2, p3 & ~mk, v2, v3);
      ok = ok && (l[h][0] <= 1.0e9f) && (l[h][2] <= 1.0e9f);
    }
    if (__builtin_expect(attempt == 1 || __all_sync(0xffffffffu, ok), 1)) break;
    const float z[4] = {0.f, 0.f, 0.f, 0.f};
#pragma unroll
    for (int h = 0; h < 4; h++) { c[h][0] = -INFINITY; c[h][2] = -INFINITY; }
#pragma unroll 1
    for (int t = 16; t >= tmin; t--) {
      const bool a = (t == 16) ? pA : (t != 0 || !pA), bb = (t == 16) ? pB : (t != 0 || !pB);
#pragma unroll
      for (int h = 0; h < 4; h++) {
        float d[8];
        sblock(d, qf[h], kaddr + h * 256 + t * 4096, z);
        if (a) { c[h][0] = fmaxf(c[h][0], d[0]); c[h][2] = fmaxf(c[h][2], d[6]); }
        if (bb) { c[h][0] = fmaxf(c[h][0], d[1]); c[h][2] = fmaxf(c[h][2], d[7]); }
        if (t != 0) c[h][2] = fmaxf(c[h][2], fmaxf(d[2], d[3]));
        if (t != 16) c[h][0] = fmaxf(c[h][0], fmaxf(d[4], d[5]));
      }
    }
#pragma unroll
    for (int h = 0; h < 4; h++) {
      float m0 = c[h][0], m1 = c[h][2];
      m0 = fmaxf(m0, __shfl_xor_sync(0xffffffffu, m0, 1)); m1 = fmaxf(m1, __shfl_xor_sync(0xffffffffu, m1, 1));
      m0 = fmaxf(m0, __shfl_xor_sync(0xffffffffu, m0, 2)); m1 = fmaxf(m1, __shfl_xor_sync(0xffffffffu, m1, 2));
      c[h][0] = -m0; c[h][1] = -m0; c[h][2] = -m1; c[h][3] = -m1;
    }
  }
#pragma unroll
  for (int h = 0; h < 4; h++) {
    float i0, i1;
    asm("rcp.approx.ftz.f32 %0, %1;" : "=f"(i0) : "f"(l[h][0]));
    asm("rcp.approx.ftz.f32 %0, %1;" : "=f"(i1) : "f"(l[h][2]));
    o0[h][0] *= i0; o0[h][1] *= i0; o1[h][0] *= i0; o1[h][1] *= i0;
    o0[h][2] *= i1; o0[h][3] *= i1; o1[h][2] *= i1; o1[h][3] *= i1;
  }
  const uint32_t t0 = q4 == 0, t1 = q4 == 1, t2 = q4 == 2, t3 = q4 == 3;
#pragma unroll
  for (int h = 0; h < 4; h += 2) {
    stg128_ll(go + h * 256, tagw(pack_bf16(o0[h][0], o0[h][1]), tag, t0), tagw(pack_bf16(o1[h][0], o1[h][1]), tag, t1),
              tagw(pack_bf16(o0[h + 1][0], o0[h + 1][1]), tag, t2), tagw(pack_bf16(o1[h + 1][0], o1[h + 1][1]), tag, t3));
    stg128_ll(go + h * 256 + 1024, tagw(pack_bf16(o0[h][2], o0[h][3]), tag, t0), tagw(pack_bf16(o1[h][2], o1[h][3]), tag, t1),
              tagw(pack_bf16(o0[h + 1][2], o0[h + 1][3]), tag, t2), tagw(pack_bf16(o1[h + 1][2], o1[h + 1][3]), tag, t3));
  }
  __syncwarp();
  if (lane == 0) red_relaxed(hint);
  mbar_wait(sb + SM_BAR + B_AUX * 8, 0);
  float a0 = 0.f, a1 = 0.f;
#pragma unroll
  for (int h = 0; h < 4; h++) {
    const float2 u = lds64f(sb + SM_WB + (h * 16 + q4 * 2) * 4), v = lds64f(sb + SM_WB + (h * 16 + 8 + q4 * 2) * 4);
    a0 += o0[h][0] * u.x + o0[h][1] * u.y + o1[h][0] * v.x + o1[h][1] * v.y;
    a1 += o0[h][2] * u.x + o0[h][3] * u.y + o1[h][2] * v.x + o1[h][3] * v.y;
  }
  a0 += __shfl_xor_sync(0xffffffffu, a0, 1); a1 += __shfl_xor_sync(0xffffffffu, a1, 1);
  a0 += __shfl_xor_sync(0xffffffffu, a0, 2); a1 += __shfl_xor_sync(0xffffffffu, a1, 2);
  pm0 += a0; pm1 += a1;
}

__device__ __forceinline__ void reglu_block(const float* ag, const float* au, uint32_t& lo, uint32_t& hi) {
  lo = bmul2(pack_relu(ag[0], ag[1]), pack_bf16(au[0], au[1]));
  hi = bmul2(pack_relu(ag[2], ag[3]), pack_bf16(au[2], au[3]));
}

__global__ void __launch_bounds__(384, 1) __cluster_dims__(2, 1, 1) fused_block_kernel(const __grid_constant__ Params p) {
  extern __shared__ __align__(1024) uint8_t smem[];
  uint32_t sb = (uint32_t)__cvta_generic_to_shared(smem);
#define NEW_PHASE() asm volatile("mov.u32 %1, %%tid.x;" : "+r"(sb), "=r"(tid))
  int tid = threadIdx.x;
  const int warp = __shfl_sync(0xffffffffu, tid >> 5, 0);
#define lane (tid & 31)
#define g ((tid & 31) >> 2)
#define q4 (tid & 3)
  const int cta = blockIdx.x, b = cta >> 3, j = cta & 7;
  const int kb0 = j & 6;
  const int hf = j & 1, pi = j >> 1;
  auto bar = [&](int i) { return sb + SM_BAR + i * 8; };

  auto opaque = [](int v) { asm volatile("" : "+r"(v)); return v; };
  if (opaque(warp >> 3)) {
    asm volatile("setmaxnreg.dec.sync.aligned.u32 40;");
    if (opaque(warp == 8)) {
      if (lane == 0) PROF(0);
      if (elect_one()) {
        mbar_init(bar(0), 1);
        fence_async_smem();
        mbar_expect(bar(B_FULLA), 32768);
        tma2d(sb + SM_X, &p.tm_x, 0, b * 128, bar(B_FULLA));
        tma2d(sb + SM_X + 16384, &p.tm_x, 64, b * 128, bar(B_FULLA));
#pragma unroll
        for (int i = 1; i < 31; i++) mbar_init(bar(i), ((0x5C23C000u >> i) & 1) ? 8 : 1);
        asm volatile("fence.mbarrier_init.release.cluster;" ::: "memory");
        fence_async_smem();
      }
      __syncwarp();
      nb_arrive(0, 384);
      asm volatile("barrier.cluster.arrive.relaxed.aligned;" ::: "memory");
      unsigned epoch = 0;
      if (elect_one()) {
#pragma unroll
        for (int i = 1; i < 4; i++) {
          mbar_expect(bar(B_FULLA + i), 32768);
          tma2d(sb + SM_X + (2 * i) * 16384, &p.tm_x, (2 * i) * 64, b * 128, bar(B_FULLA + i));
          tma2d(sb + SM_X + (2 * i + 1) * 16384, &p.tm_x, (2 * i + 1) * 64, b * 128, bar(B_FULLA + i));
        }
#pragma unroll
        for (int c = 0; c < 12; c++) {
          if (c == 4) {
            mbar_expect(bar(B_RECV), 16384);
            bulk_prefetch((const uint8_t*)p.wqkv + cta * 12288, 12288);
            mbar_wait(bar(B_CDONE), 0);
          }
          const uint32_t fb = bar(B_FULLW + (c == 1 ? 1 : c >> 1));
          if (c < 2 || (c >= 4 && (c & 1) == 0)) mbar_expect(fb, c == 0 ? 16384 : (c == 1 ? 49152 : 32768));
          tma2d(sb + SM_WK - (c >> 2) * 65536 + (c & 3) * 16384, &p.tm_qkv, (c < 8 ? 512 + (c >> 2) * 512 : 0) + j * 64, (c & 3) * 128, fb);
        }
        epoch = atomicAdd(&g_ticket[0], 1u) / NCTA;
        sts32(sb + SM_EPOCH, epoch);
        bulk_prefetch((const uint8_t*)p.wo + cta * 4096, 4096);
#pragma unroll
        for (int i = 0; i < 6; i++) prefetch_tm(&p.tm_wo + i);
        mbar_wait(bar(B_CDONE), 1);
      }
      __syncwarp();
      epoch = lds32(sb + SM_EPOCH);
      if (elect_one()) {
#pragma unroll
        for (int i = 0; i < 2; i++)
          if (b <= i) {
            mbar_arrive(bar(B_KV1 + i));
          } else {
            mbar_expect(bar(B_KV1 + i), 32768);
            if (i == 1) mbar_wait(bar(B_KV1), 0);
            poll_flag(&g_flag[cta - 8 - 8 * i][0], epoch + 1);
            fence_async_global();
            bulk_g2s(sb + SM_KV + (1 - i) * 32768, g_kv[cta - 8 - 8 * i], 32768, bar(B_KV1 + i));
          }
        mbar_expect(bar(B_WO), 131072);
        mbar_wait(bar(B_CDONE), 0);
        mbar_wait(bar(B_KV1), 0);
        mbar_wait(bar(B_KV2), 0);
#pragma unroll
        for (int c = 0; c < 4; c++) tma5d(sb + wopiece(c >> 1, c & 1), &p.tm_wo, kb0 * 64 + (c >> 1) * 64, (c & 1) * 8, bar(B_WO));
        bulk_prefetch((const uint8_t*)p.wg + cta * 14336, 14336);
        bulk_prefetch((const uint8_t*)p.wu + cta * 14336, 14336);
        bulk_prefetch((const uint8_t*)p.wd + cta * 14336, 14336);
#pragma unroll
        for (int c = 0; c < 4; c++) mbar_expect(bar(B_FULLA + 4 + c), 16384);
      }
      __syncwarp();
      mbar_wait(bar(B_CDONE), 1);
      if (lane < 8) poll_flag(&g_flag[b * 8 + lane][1], 8 * (epoch + 1));
      __syncwarp();
      if (elect_one()) {
        const uint8_t* src = g_o[b * 8] + hf * 8192;
#pragma unroll
        for (int c = 0; c < 8; c++) { if (c == 4) mbar_wait(bar(B_FULLA + 4), 0); bulk_g2s(sb + SM_O + c * 8192, src + c * 16384, 8192, bar(B_FULLA + 4 + (c >> 1))); }
        PROF(23);
        int sl = 0;
#pragma unroll
        for (int n = 0; n < 16; n++) {
          if (n < 12) mbar_wait(bar(n < 4 ? (n < NEARLY ? B_OHALF : B_ODONE) : B_DONES + (n < 5 ? 0 : (n == 7 ? 2 : (n < 9 ? n - 4 : n - 3)))), 0);
          else mbar_wait(bar(B_EMPTYC + sl), n == 15);
          const uint32_t d = sb + (n == 0 ? cslot(2) : (n < 9 ? cstage(n - 1) : cslot(sl)));
          const uint32_t fb = bar(n < 9 ? B_FULLS + n : B_FULLC + sl);
          if (n < 9 && n != 0) {
            const int k0 = ((kb0 + n - 1) & 7) * 64;
            mbar_expect(fb, 24576);
            tma3d(d, &p.tm_g2, j * 224 + (hf ? 0 : 128), k0, 0, fb);
            tma3d(d + 12288, &p.tm_u2, j * 224 + (hf ? 0 : 128), k0, 0, fb);
          } else {
            const int k0 = ((kb0 + 2 * n) & 7) * 64, c0 = j * 224 + hf * 96 + (n >= 12 ? 64 : 0);
            mbar_expect(fb, 32768);
            tma2d(d, &p.tm_g1, c0, k0, fb);
            tma2d(d + 16384, &p.tm_u1, c0, k0, fb);
          }
          sl = (sl == 2) ? 0 : sl + 1;
        }
#pragma unroll
        for (int u = 0; u < 8; u++) {
          const uint32_t d = sb + ((0x35621403u >> (4 * u)) & 15) * 32768;
          const uint32_t fb = bar(8 + ((0x1001000f03110210ull >> (8 * u)) & 255));
          mbar_wait(bar(14 + ((0xD10C3E2Du >> (4 * u)) & 15)), (0x65u >> u) & 1);
          mbar_expect(fb, 28672);
          tma2d(d, &p.tm_d, hf * 256 + ((pi + 1 + (u >> 1)) & 3) * 64, (j ^ (u & 1)) * 224, fb);
        }
        const uint8_t* ps = g_p[cta][0];
        mbar_expect(bar(B_FULLA), 49152);
        mbar_wait(bar(B_EMPTYA + 2), 1);
        bulk_g2s(sb + aslot(2), g_h[b * 8 + hf * 4 + pi], 16384, bar(B_FULLA));
        poll_flag(&g_flag[cta][4], 8 * (epoch + 1));
        bulk_g2s(sb + aslot(2) + 16384, ps, 16384, bar(B_FULLA));
        mbar_wait(bar(B_EMPTYA + 3), 1);
        poll_flag(&g_flag[cta][5], 8 * (epoch + 1));
        bulk_g2s(sb + aslot(2) + 32768, ps + 16384, 16384, bar(B_FULLA));
      }
    } else {
      const int hw = warp - 9;
      if (hw == 0 && elect_one()) {
#pragma unroll
        for (int i = 32; i < 70; i++) mbar_init(bar(i), (i < B_DONES || i >= B_HP) ? 1 : (i == B_DONES + 3 ? 16 : 8));
        asm volatile("fence.mbarrier_init.release.cluster;" ::: "memory");
        fence_async_smem();
#pragma unroll
        for (int i = 0; i < 6; i++) mbar_expect(bar(B_HP + i), 16384);
      }
      __syncwarp();
      asm volatile("barrier.cluster.arrive.relaxed.aligned;" ::: "memory");
      nb_sync(0, 384);
      mbar_wait(bar(B_FULLW + 5), 0);
      if (opaque(hw == 0)) {
        nb_sync(NB_RELKV, 256 + 32);
        if (lane == 0) red_release(&g_flag[cta][0]);
        mbar_wait(bar(B_ODONE), 0);
        const unsigned epoch = lds32(sb + SM_EPOCH);
        if (lane < 8) poll_flag(&g_flag[b * 8 + lane][2], 8 * (epoch + 1));
        __syncwarp();
        if (elect_one()) {
          PROF(22);
#pragma unroll
          for (int kp = 2; kp < 8; kp++) {
            if (kp >= 4) mbar_wait(bar(B_HP + kp - 4), 0);
            if (kp == 6) mbar_wait(bar(B_DONES + 3), 0);
            bulk_g2s_pair(sb + aslot(kp >> 1) + (kp & 1) * 16384 + hf * 8192, g_h[b * 8 + ((kb0 + kp) & 7)] + hf * 8192, 8192, bar(B_HP + kp - 2));
          }
        }
        if (elect_one()) { mbar_wait(bar(B_RECV), 0); mbar_expect(bar(B_RECV), 40960); mbar_expect(bar(B_WO), 16384); }
      } else {
        const int h2 = hw - 1;
        const int wr = b * 4 + h2 * 2 + (lane >> 4);
        float ws = 0.f;
        {
          const __nv_bfloat16* src = p.wo + (size_t)(j * 64 + wr) * DM + (lane & 15) * 8;
          uint4 v[4];
#pragma unroll
          for (int r = 0; r < 4; r++) v[r] = ldg128_nc(src + r * 128);
#pragma unroll
          for (int r = 0; r < 4; r++)
            ws += (bf_lo(v[r].x) + bf_hi(v[r].x)) + (bf_lo(v[r].y) + bf_hi(v[r].y)) + (bf_lo(v[r].z) + bf_hi(v[r].z)) + (bf_lo(v[r].w) + bf_hi(v[r].w));
#pragma unroll
          for (int o = 8; o > 0; o >>= 1) ws += __shfl_xor_sync(0xffffffffu, ws, o);
        }
        mbar_wait(bar(B_KV1), 0);
        const unsigned epoch = lds32(sb + SM_EPOCH);
        if ((lane & 15) == 0)
          asm volatile("st.relaxed.gpu.global.u32 [%0], %1;" ::"l"(&g_wb[j][wr]), "r"(tagw(__float_as_uint(ws * (1.f / DM)), epoch + 1, 1)) : "memory");
        if (h2 == 0) {
          uint2 w;
          int it = 0;
          do { __nanosleep(400); w = ldg64_ll(&g_wb[j][lane * 2]); } while ((((w.x ^ (epoch + 1)) | (w.y ^ (epoch + 1))) & 1) && ++it < (1 << 16));
          sts64f(sb + SM_WB + lane * 8, make_float2(__uint_as_float(w.x), __uint_as_float(w.y)));
          __syncwarp();
          if (lane == 0) { mbar_arrive(bar(B_AUX)); PROF(19); }
        }
#pragma unroll 1
        for (int kp = 2; kp < 8; kp++) {
          const uint32_t hs = sb + aslot(kp >> 1) + (kp & 1) * 16384 + h2 * 8192 + lane * 16;
          mbar_wait(bar(B_HP + kp - 2), 0);
          if (__builtin_expect(stale_smem<16>(hs + (lane >> 3) * 4, 512, epoch + 1) != 0, 0)) {
            CNT(1);
            repair(hs, g_h[b * 8 + ((kb0 + kp) & 7)] + h2 * 8192 + lane * 16, 16, 512, 512, epoch + 1);
          }
          __syncwarp();
          if (lane == 0) mbar_arrive(bar(B_HV + 2 * (kp - 2) + h2));
        }
      }
    }
    __syncwarp();
    asm volatile("barrier.cluster.wait.acquire.aligned;" ::: "memory");
  } else {
    asm volatile("barrier.cluster.arrive.relaxed.aligned;" ::: "memory");
    asm volatile("setmaxnreg.inc.sync.aligned.u32 232;");
    const int wg = warp >> 2;
    const uint32_t peer = (uint32_t)(hf ^ 1);
    const uint32_t ONES = 0x3f803f80u;
    const int tile = wg ? 11 - warp : warp;
    nb_sync(0, 384);
    uint32_t qf[4][4];
    float pm0, pm1;
    {
      uint32_t xa[32][4];
      float rs0, rs1;
      float accX[32], accY[32];
      {
        float sa[2][4] = {}, va[2][4] = {}, vb[2][4] = {};
        const uint32_t xrow = sb + SM_X + (tile * 16 + (lane & 15)) * 128;
#pragma unroll
        for (int k8 = 0; k8 < 32; k8 += 8) {
          mbar_wait(bar(B_FULLA + (k8 >> 3)), 0);
          if (k8 == 0) PROFT(0, 17);
#pragma unroll
          for (int k = k8; k < k8 + 8; k++) {
            ldsm4(xrow + (k >> 2) * 16384 + ((((k & 3) * 2 + (lane >> 4)) ^ (lane & 7)) << 4), xa[k][0], xa[k][1], xa[k][2], xa[k][3]);
          }
          if (k8 == 24) { __syncwarp(); if (lane == 0) mbar_arrive(bar(B_CDONE)); }
#pragma unroll
          for (int k = k8; k < k8 + 8; k++) {
            mma_acc(sa[k & 1], xa[k][0], xa[k][1], xa[k][2], xa[k][3], ONES, ONES);
            mma_k8(va[0], xa[k][0], xa[k][1], xa[k][0]); mma_k8(vb[0], xa[k][0], xa[k][1], xa[k][1]);
            mma_k8(va[1], xa[k][2], xa[k][3], xa[k][2]); mma_k8(vb[1], xa[k][2], xa[k][3], xa[k][3]);
          }
        }
        const float mean0 = (sa[0][0] + sa[1][0]) * (1.f / DM), mean1 = (sa[0][2] + sa[1][2]) * (1.f / DM);
        const uint32_t h0 = pack_bf16(mean0, mean0), h1 = pack_bf16(mean1, mean1);
        pm0 = mean0 * 0.125f; pm1 = mean1 * 0.125f;
        const float e0 = __shfl_sync(0xffffffffu, (g & 1) ? va[0][1] + va[1][1] : va[0][0] + va[1][0], (lane & 28) + (g >> 1));
        const float e1 = __shfl_sync(0xffffffffu, (g & 1) ? vb[0][3] + vb[1][3] : vb[0][2] + vb[1][2], (lane & 28) + (g >> 1));
        rs0 = rsqrtf(fmaxf(e0 * (1.f / DM) - mean0 * mean0, 0.f) + LN_EPS);
        rs1 = rsqrtf(fmaxf(e1 * (1.f / DM) - mean1 * mean1, 0.f) + LN_EPS);
        PROFT(0, 1);
        const uint64_t db = mkdesc(sb + SM_WK, 8192, 1024, 1);
#pragma unroll
        for (int kb = 0; kb < 8; kb++) {
#pragma unroll
          for (int k = 4 * kb; k < 4 * kb + 4; k++) {
            xa[k][0] = bsub2(xa[k][0], h0); xa[k][1] = bsub2(xa[k][1], h1); xa[k][2] = bsub2(xa[k][2], h0); xa[k][3] = bsub2(xa[k][3], h1);
          }
          if (kb == 0 || kb == 2) mbar_wait(bar(B_FULLW + (kb >> 1)), 0);
          wg_fence();
#pragma unroll
          for (int k = 4 * kb; k < 4 * kb + 4; k++) wgmma_rs_n64(accX, xa[k][0], xa[k][1], xa[k][2], xa[k][3], db + k * 128, k != 0);
        }
        wg_commit();
      }
      NEW_PHASE();
      uint8_t* gkv = g_kv[cta] + tile * 4096 + lane * 4;
      const uint32_t skv = sb + SM_KV + 65536 + tile * 4096 + lane * 4;
#pragma unroll
      for (int ps = 0; ps < 2; ps++) {
        const uint64_t db = mkdesc(sb + (ps == 0 ? SM_WV : SM_WQ), 8192, 1024, 1);
#pragma unroll
        for (int k = 0; k < 32; k++) {
          if ((k & 15) == 0) { mbar_wait(bar(B_FULLW + 2 + ps * 2 + (k >> 4)), 0); wg_fence(); }
          if (ps == 0) wgmma_rs_n64(accY, xa[k][0], xa[k][1], xa[k][2], xa[k][3], db + k * 128, k != 0);
          else wgmma_rs_n64(accX, xa[k][0], xa[k][1], xa[k][2], xa[k][3], db + k * 128, k != 0);
          if (k == 2) {
            wg_commit();
            wg_wait<1>();
            if (ps == 0) { pin(accX); if (lane == 0) mbar_arrive(bar(B_CDONE)); PROFT(0, 2); } else { pin(accY); PROFT(0, 3); }
            wg_fence();
          }
          const int sp = (ps == 0) ? KSP : VSP;
          if (k >= 2 && (k - 2) % sp == 0 && (k - 2) / sp < 8) {
            const float* a = (ps == 0) ? accX : accY;
            const int i = (k - 2) / sp;
            const uint32_t lo = pack_bf16(rs0 * a[4 * i], rs0 * a[4 * i + 1]), hi = pack_bf16(rs1 * a[4 * i + 2], rs1 * a[4 * i + 3]);
            stg32(gkv + (ps * 8 + i) * 128, lo); stg32(gkv + 2048 + (ps * 8 + i) * 128, hi);
            sts32(skv + (ps * 8 + i) * 128, lo); sts32(skv + 2048 + (ps * 8 + i) * 128, hi);
            if (ps == 1 && i == 7) nb_arrive(NB_RELKV, 256 + 32);
          }
        }
        wg_commit();
      }
      wg_wait<0>();
      pin(accX);
      if (lane == 0) mbar_arrive(bar(B_CDONE));
      nb_sync(NB_CONS, 256);
      const float QS = 0.25f * 1.4426950408889634f;
      const float r0 = rs0 * QS, r1 = rs1 * QS;
#pragma unroll
      for (int i = 0; i < 8; i++) {
        qf[i >> 1][(i & 1) * 2] = pack_bf16(r0 * accX[4 * i], r0 * accX[4 * i + 1]);
        qf[i >> 1][(i & 1) * 2 + 1] = pack_bf16(r1 * accX[4 * i + 2], r1 * accX[4 * i + 3]);
      }
    }
    NEW_PHASE();
    PROFT(0, 5);
    uint32_t tag;
    const int prow = hf * 64 + (warp & 3) * 16;
    attention(sb, qf, b, tile, lane, g_o[cta] + tile * 2048 + q4 * 128 + g * 16, tag, &g_flag[cta][1], pm0, pm1);
    if (q4 == 0) stg64_ll(&g_om[cta][tile * 8 + g], tagw(__float_as_uint(pm0), tag, 1), __float_as_uint(pm1));
    NEW_PHASE();
    PROFT(0, 6);
    asm volatile("barrier.cluster.wait.acquire.aligned;" ::: "memory");
    if (lane == 0) mbar_arrive_remote(mapa(bar(B_PEER), peer));
    uint32_t xres[16];
    {
      const __nv_bfloat16* xs = p.x + (size_t)(b * 128 + prow + g) * DM + (kb0 + wg) * 64 + q4 * 2;
#pragma unroll
      for (int i = 0; i < 8; i++) { xres[2 * i] = ldg32_nc(xs + i * 8); xres[2 * i + 1] = ldg32_nc(xs + 8 * DM + i * 8); }
    }
    {
      float acc[32];
      mbar_wait(bar(B_WO), 0);
      const uint64_t dwo = mkdesc(sb + wopiece(wg, 1), 8192, 1024, 1), dao = mkdesc(sb + SM_O, 128, 1024, 0);
#pragma unroll
      for (int i = 0; i < 16; i++) { acc[2 * i] = bf_lo(xres[i]); acc[2 * i + 1] = bf_hi(xres[i]); }
      pin(acc);
      bool bad = false;
      const uint2* mp = &g_om[b * 8 + q4 * 2][(prow >> 1) + g];
      uint2 u0 = make_uint2(0u, 0u), u1 = u0;
      float acc2[32];
      uint32_t bad2 = 0;
#pragma unroll
      for (int i = 0; i < 4; i++) {
        mbar_wait(bar(B_FULLA + 4 + i), 0);
        if (i == 0) PROFT(0, 7);
        wg_fence();
#pragma unroll
        for (int k = 8 * i; k < 8 * i + 8; k++) {
          if (k < 16) wgmma_ss_n64(acc, dao + (k >> 2) * 512 + (k & 3) * 16, dwo + 4096 + k * 128, 1);
          else wgmma_ss_n64(acc2, dao + (k >> 2) * 512 + (k & 3) * 16, dwo + (k & 15) * 128, k != 16);
          if (k == 10) bad = __any_sync(0xffffffffu, stale_smem<8>(sb + SM_O + tid * 16 + (lane >> 3) * 4, 4096, tag) != 0);
          if (k == 26) { bad2 = stale_smem<8>(sb + SM_O + 32768 + tid * 16 + (lane >> 3) * 4, 4096, tag); u0 = ldg64_ll(mp); u1 = ldg64_ll(mp + 64); }
          if (k == 17) {
            wg_commit();
            wg_wait<1>();
            if (lane == 0 && !bad) mbar_arrive(bar(B_OHALF));
            wg_fence();
          }
        }
        wg_commit();
      }
      mbar_wait(bar(B_PEER), 0);
      const bool redo = nb_any(NB_CONS, 256, bad || bad2);
      wg_wait<0>();
      pin(acc); pin(acc2);
      if (__builtin_expect(redo, 0)) {
        CNT(0);
        const int s0 = nb_any(NB_CONS, 256, bad) ? 0 : 4;
        repair(sb + SM_O + s0 * 8192 + tid * 16, g_o[b * 8 + s0] + hf * 8192 + tid * 16, 8 - s0, 8192, 16384, tag);
        repair(sb + SM_O + s0 * 8192 + 4096 + tid * 16, g_o[b * 8 + s0] + hf * 8192 + 4096 + tid * 16, 8 - s0, 8192, 16384, tag);
        nb_sync(NB_CONS, 256);
#pragma unroll 1
        for (int s = s0; s < 8; s++) {
          wg_fence();
#pragma unroll
          for (int k = 0; k < 4; k++) wgmma_ss_n64(acc2, dao + s * 512 + k * 16, dwo + (s < 4 ? 4096 : 0) + ((s & 3) * 4 + k) * 128, s != s0 || k != 0);
          wg_commit();
          wg_wait<0>();
        }
        pin(acc2);
        if (s0 == 0) {
#pragma unroll
          for (int i = 0; i < 16; i++) {
            asm volatile("add.u32 %0, %0, 0;" : "+r"(xres[i]));
            acc[2 * i] = bf_lo(xres[i]); acc[2 * i + 1] = bf_hi(xres[i]);
          }
        }
        nb_sync(NB_CONS, 256);
        if (lane == 0 && bad) mbar_arrive(bar(B_OHALF));
      }
      PROFT(0, 8);
      for (int it = 0; (((u0.x ^ tag) | (u1.x ^ tag)) & 1) && it < (1 << 17); it++) { CNT(5); u0 = ldg64_ll(mp); u1 = ldg64_ll(mp + 64); }
      __syncwarp();
      float s0 = __uint_as_float(u0.x) + __uint_as_float(u1.x), s1 = __uint_as_float(u0.y) + __uint_as_float(u1.y);
      s0 += __shfl_xor_sync(0xffffffffu, s0, 1); s1 += __shfl_xor_sync(0xffffffffu, s1, 1);
      s0 += __shfl_xor_sync(0xffffffffu, s0, 2); s1 += __shfl_xor_sync(0xffffffffu, s1, 2);
      const uint32_t hoff = wg * 16384 + prow * 128 + lane * 4;
      const uint32_t sh = sb + SM_HE + hoff;
#pragma unroll
      for (int i = 0; i < 8; i++) {
        xres[2 * i] = tagw(pack_bf16((acc[4 * i] + acc2[4 * i]) - s0, (acc[4 * i + 1] + acc2[4 * i + 1]) - s0), tag, q4 == (i & 3));
        xres[2 * i + 1] = tagw(pack_bf16((acc[4 * i + 2] + acc2[4 * i + 2]) - s1, (acc[4 * i + 3] + acc2[4 * i + 3]) - s1), tag, q4 == (i & 3));
        sts32(sh + i * 128, xres[2 * i]); sts32(sh + 1024 + i * 128, xres[2 * i + 1]);
      }
      PROFT(0, 30);
      fence_async_smem();
      __syncwarp();
      PROFT(0, 26);
      if (elect_one()) {
        const uint32_t sw = sb + SM_HE + wg * 16384 + prow * 128;
        bulk_s2g(g_h[b * 8 + kb0] + wg * 16384 + prow * 128, sw, 2048);
        bulk_s2peer(mapa(sw, peer), sw, 2048, mapa(bar(B_RECV), peer));
        mbar_arrive(bar(B_ODONE));
      }
      __syncwarp();
      PROFT(0, 24);
      PROFT(0, 18);
      float qa[4] = {0.f, 0.f, 0.f, 0.f}, qb[4] = {0.f, 0.f, 0.f, 0.f};
#pragma unroll
      for (int k = 0; k < 8; k++) { mma_k8(qa, xres[2 * k], xres[2 * k + 1], xres[2 * k]); mma_k8(qb, xres[2 * k], xres[2 * k + 1], xres[2 * k + 1]); }
      if (q4 == (g >> 1))
        stg128_ll(&g_stat2[b * 8 + kb0 + wg][(prow >> 1) + g], tagw(__float_as_uint(s0), tag, 1), __float_as_uint((g & 1) ? qa[1] : qa[0]), __float_as_uint(s1),
                  __float_as_uint((g & 1) ? qb[3] : qb[2]));
      if (lane == 0) red_relaxed(&g_flag[cta][2]);
      PROFT(0, 21);
      nb_sync(NB_CONS, 256);
      if (wg != hf) mbar_wait(bar(B_RECV), 0);
    }
    NEW_PHASE();
    PROFT(0, 9);
    uint32_t own[56];
    float2 st0, st1;
    float accC[96], accA[64];
    float accB[64];
    {
      {
        const uint64_t da = mkdesc(sb + aslot(0) + wg * 8192, 128, 1024, 0);
        const uint64_t db = mkdesc(sb + cslot(2), 16384, 1024, 1), dc = mkdesc(sb + cslot(0), 4096, 512, 2);
        mbar_wait(bar(B_FULLS), 0);
        wg_fence();
#pragma unroll
        for (int k = 0; k < 8; k++) wgmma_ss_n128(accA, da + (k >> 2) * 1024 + (k & 3) * 16, db + k * 128, k != 0);
        wg_commit();
        mbar_wait(bar(B_FULLS + 1), 0);
        wg_fence();
#pragma unroll
        for (int k = 0; k < 4; k++) wgmma_ss_n192(accC, da + k * 16, dc + k * 64, k != 0);
        wg_commit();
        wg_wait<1>();
        pin(accA);
        if (lane == 0) mbar_arrive(bar(B_DONES));
      }
      const uint4* sp = &g_stat2[b * 8 + q4 * 2][warp * 8 + g];
      uint4 t0 = make_uint4(0u, 0u, 0u, 0u), t1 = t0;
      PROFT(0, 31);
#pragma unroll
      for (int kp = 1; kp < 8; kp++) {
        if (kp >= 2) mbar_wait(bar(B_HV + 2 * (kp - 2) + wg), 0);
        if (kp == 2) PROFT(0, 20);
        mbar_wait(bar(B_FULLS + 1 + kp), 0);
        if (kp == 2) PROFT(0, 4);
        if (kp == 4) PROFT(0, 10);
        wg_fence();
        const uint64_t da = mkdesc(sb + aslot(kp >> 1) + (kp & 1) * 16384 + wg * 8192, 128, 1024, 0);
        const uint64_t db = mkdesc(sb + cstage(kp), 4096, 512, 2);
#pragma unroll
        for (int k = 0; k < 4; k++) wgmma_ss_n192(accC, da + k * 16, db + k * 64, 1);
        wg_commit();
        if (kp == 5) { t0 = ldg128_ll(sp); t1 = ldg128_ll(sp + 64); }
        wg_wait<1>();
        if (lane == 0) { mbar_arrive(bar(B_DONES + kp)); if (kp == 3) mbar_arrive_remote(mapa(bar(B_DONES + 3), peer)); }
      }
#pragma unroll
      for (int n = 9; n < 16; n++) {
        const int m = n & 3;
        NEW_PHASE();
        mbar_wait(bar(B_FULLC + n % 3), (n / 3 + 1) & 1);
        const uint64_t da = mkdesc(sb + aslot(m) + wg * 8192, 128, 1024, 0);
        const uint64_t db = mkdesc(sb + cslot(n % 3), 16384, 1024, 1);
#pragma unroll
        for (int k2 = 0; k2 < 4; k2++) {
          wg_fence();
#pragma unroll
          for (int k = 2 * k2; k < 2 * k2 + 2; k++) {
            if (n < 12) wgmma_ss_n128(accA, da + (k >> 2) * 1024 + (k & 3) * 16, db + k * 128, 1);
            else wgmma_ss_n128(accB, da + (k >> 2) * 1024 + (k & 3) * 16, db + k * 128, (m | k) != 0);
          }
          if (k2 == 0 || k2 == 3) wg_commit();
          if (k2 == 0) {
            wg_wait<1>();
            if (lane == 0) {
              mbar_arrive(bar(n == 9 ? B_DONES + 8 : B_EMPTYC + (n - 1) % 3));
              if (n >= 13) mbar_arrive(bar(B_EMPTYA + n - 13));
              if (n == 13) mbar_arrive_remote(mapa(bar(B_PEER), peer));
              if (n == 14) mbar_arrive_remote(mapa(bar(B_CDONE), peer));
            }
            if (n == 9) {
              pin(accC);
              PROFT(0, 11);
      {
        for (int it = 0; (((t0.x ^ tag) | (t1.x ^ tag)) & 1) && it < (1 << 17); it++) { CNT(4); t0 = ldg128_ll(sp); t1 = ldg128_ll(sp + 64); }
        __syncwarp();
        const float m0 = __uint_as_float(t0.x), m1 = __uint_as_float(t0.z);
        float v0 = __uint_as_float(t0.y) + __uint_as_float(t1.y), v1 = __uint_as_float(t0.w) + __uint_as_float(t1.w);
        v0 += __shfl_xor_sync(0xffffffffu, v0, 1); v1 += __shfl_xor_sync(0xffffffffu, v1, 1);
        v0 += __shfl_xor_sync(0xffffffffu, v0, 2); v1 += __shfl_xor_sync(0xffffffffu, v1, 2);
        st0 = make_float2(m0, __fdividef(1.f, v0 * (1.f / DM) + LN_EPS));
        st1 = make_float2(m1, __fdividef(1.f, v1 * (1.f / DM) + LN_EPS));
      }
            }
            if (n == 12) { pin(accA); PROFT(0, 12); }
          }
          if (n < 12) {
            const int i = (n - 9) * 4 + k2;
            reglu_block(&accC[4 * i], &accC[48 + 4 * i], own[2 * i], own[2 * i + 1]);
          } else if (n < 14) {
            const int i = m * 4 + k2;
            reglu_block(&accA[4 * i], &accA[32 + 4 * i], own[24 + 2 * i], own[25 + 2 * i]);
          }
          if (n >= 13 && (n - 13) * 4 + k2 >= 2) {
            const int v = (n - 13) * 4 + k2 - 2;
            if (v == 0) mbar_wait(bar(B_PEER), 1);
            if (v == 6) mbar_wait(bar(B_CDONE), 0);
            const uint32_t rb = mapa(sb, peer);
            st_async128(rb + (v < 6 ? aslot(0) + v * 4096 : aslot(1) + (v - 6) * 4096) + tid * 16, &own[4 * v], rb + SM_BAR + B_RECV * 8);
          }
        }
      }
    }
    NEW_PHASE();
    {
      uint32_t oth[56];
      float accP[32];
      float accQ[32];
      auto krow = [](int v, int e) { return v < 6 ? (e ? 0 : 128) + v * 16 : e * 96 + (v - 6) * 16; };
      {
        const uint64_t d0 = mkdesc(sb + cslot(1), 8192, 1024, 1), d1 = mkdesc(sb + aslot(2), 8192, 1024, 1);
        const uint32_t rb = mapa(sb, peer);
        mbar_wait(bar(B_FULLC + 1), 0);
#pragma unroll
        for (int c = 0; c < 6; c++) {
          if (c == 2 || c == 4) {
            if (c == 2) mbar_wait(bar(B_RECV), 1);
#pragma unroll
            for (int v = (c == 2 ? 0 : 6); v < (c == 2 ? 6 : 10); v++) {
              const uint4 t = lds128(sb + (v < 6 ? aslot(0) + v * 4096 : aslot(1) + (v - 6) * 4096) + tid * 16);
              oth[4 * v] = t.x; oth[4 * v + 1] = t.y; oth[4 * v + 2] = t.z; oth[4 * v + 3] = t.w;
            }
            if (c == 2) {
              __syncwarp();
              if (lane == 0) mbar_arrive(bar(B_EMPTYA + 0));
              mbar_wait(bar(B_FULLW + 2), 1);
            }
          }
          wg_fence();
#pragma unroll
          for (int e = 0; e < 4; e++) {
            const int x = c * 4 + e;
            if (x < 10) wgmma_rs_n64(accP, own[4 * x], own[4 * x + 1], own[4 * x + 2], own[4 * x + 3], d0 + krow(x, hf) * 8, x != 0);
            else if (x < 20) wgmma_rs_n64(accP, oth[4 * x - 40], oth[4 * x - 39], oth[4 * x - 38], oth[4 * x - 37], d1 + krow(x - 10, hf ^ 1) * 8, 1);
            else wgmma_rs_n64(accP, own[4 * x - 40], own[4 * x - 39], own[4 * x - 38], own[4 * x - 37], d0 + krow(x - 10, hf) * 8, 1);
          }
          if (c == 0) {
            wg_commit();
            wg_wait<1>();
            pin(accB);
            if (lane == 0) { mbar_arrive(bar(B_EMPTYC + 0)); mbar_arrive(bar(B_EMPTYA + 3)); }
            PROFT(0, 13);
          }
          if (c < 4) {
#pragma unroll
            for (int i = 2 * c; i < 2 * c + 2; i++)
              reglu_block(&accB[4 * i], &accB[32 + 4 * i], own[40 + 2 * i], own[41 + 2 * i]);
            st_async128(rb + aslot(1) + 16384 + c * 4096 + tid * 16, &own[40 + 4 * c], rb + SM_BAR + B_WO * 8);
          }
        }
      }
      PROFT(0, 14);
      float sum[32];
      uint32_t early_bad = 0;
      uint4 pt[4];
#define psrc (g_p[cta][0] + warp * 2048 + lane * 16)
#pragma unroll
      for (int s = 1; s < 4; s++) {
        NEW_PHASE();
        const uint32_t w0 = (s == 1) ? cslot(2) : (s == 2 ? cslot(0) : aslot(1)), w1 = (s == 1) ? aslot(3) : (s == 2 ? aslot(0) : cslot(1));
        const uint64_t d0 = mkdesc(sb + w0, 8192, 1024, 1), d1 = mkdesc(sb + w1, 8192, 1024, 1);
        uint8_t* gp = g_p[b * 8 + ((pi + s) & 3) * 2 + hf][s - 1] + warp * 2048;
        const int cship = (s == 1) ? 3 : 0;
#pragma unroll
        for (int c = 0; c < 7; c++) {
          if (c == 0) {
            if (s == 1) mbar_wait(bar(B_FULLC + 2), 0);
            if (s == 2) mbar_wait(bar(B_FULLC + 0), 1);
            if (s == 3) mbar_wait(bar(B_FULLW + 1), 1);
          }
          if (c == 3) {
            if (s == 1) mbar_wait(bar(B_FULLW + 3), 1);
            if (s == 2) mbar_wait(bar(B_FULLW + 0), 1);
            if (s == 3) mbar_wait(bar(B_FULLC + 1), 1);
          }
          if (c == 0 || c == 3 || (s == 3 && c == 5)) wg_fence();
#pragma unroll
          for (int e = 0; e < 4; e++) {
            const int x = c * 4 + e;
            if (s & 1) {
              if (x < 14) wgmma_rs_n64(accQ, own[4 * x], own[4 * x + 1], own[4 * x + 2], own[4 * x + 3], d0 + krow(x, hf) * 8, x != 0);
              else wgmma_rs_n64(accQ, oth[4 * x - 56], oth[4 * x - 55], oth[4 * x - 54], oth[4 * x - 53], d1 + krow(x - 14, hf ^ 1) * 8, 1);
            } else {
              if (x < 14) wgmma_rs_n64(accP, own[4 * x], own[4 * x + 1], own[4 * x + 2], own[4 * x + 3], d0 + krow(x, hf) * 8, x != 0);
              else wgmma_rs_n64(accP, oth[4 * x - 56], oth[4 * x - 55], oth[4 * x - 54], oth[4 * x - 53], d1 + krow(x - 14, hf ^ 1) * 8, 1);
            }
          }
          if (s == 1 && c == 2) {
            mbar_wait(bar(B_WO), 1);
#pragma unroll
            for (int v = 10; v < 14; v++) {
              const uint4 t = lds128(sb + aslot(1) + (v - 6) * 4096 + tid * 16);
              oth[4 * v] = t.x; oth[4 * v + 1] = t.y; oth[4 * v + 2] = t.z; oth[4 * v + 3] = t.w;
            }
            __syncwarp();
            if (lane == 0) mbar_arrive(bar(B_EMPTYA + 1));
            const uint64_t dz = mkdesc(sb + aslot(2), 8192, 1024, 1);
            wg_fence();
#pragma unroll
            for (int v = 10; v < 14; v++) wgmma_rs_n64(accP, oth[4 * v], oth[4 * v + 1], oth[4 * v + 2], oth[4 * v + 3], dz + krow(v, hf ^ 1) * 8, 1);
            wg_commit();
          }
          if (c == cship || c == 6) wg_commit();
          if (c == cship) {
            wg_wait<1>();
            if (s & 1) pin(accP); else pin(accQ);
            if (s == 1 && lane == 0) { mbar_arrive(bar(B_EMPTYC + 1)); mbar_arrive(bar(B_EMPTYA + 2)); }
            if (s == 2 && lane == 0) mbar_arrive(bar(B_EMPTYA + 3));
            const float* a = (s & 1) ? accP : accQ;
            if (s >= TS0) {
              mbar_wait(bar(B_EMPTYA + 3), 1);
              const uint32_t stg = sb + cslot(2) + (s - 2) * 16384 + warp * 2048;
#pragma unroll
              for (int i = 0; i < 4; i++)
                sts128(stg + i * 512 + lane * 16, make_uint4(tagw(pack_bf16(a[8 * i], a[8 * i + 1]), tag, 1), pack_bf16(a[8 * i + 2], a[8 * i + 3]),
                                                            pack_bf16(a[8 * i + 4], a[8 * i + 5]), pack_bf16(a[8 * i + 6], a[8 * i + 7])));
              fence_async_smem();
              __syncwarp();
              if (elect_one()) bulk_s2g(gp, stg, 2048);
              __syncwarp();
            } else {
#pragma unroll
              for (int i = 0; i < 4; i++)
                stg128_ll(gp + i * 512 + lane * 16, tagw(pack_bf16(a[8 * i], a[8 * i + 1]), tag, 1), pack_bf16(a[8 * i + 2], a[8 * i + 3]),
                          pack_bf16(a[8 * i + 4], a[8 * i + 5]), pack_bf16(a[8 * i + 6], a[8 * i + 7]));
              if (s < 3 && lane == 0) red_relaxed(&g_flag[b * 8 + ((pi + s) & 3) * 2 + hf][3 + s]);
            }
            PROFT(0, 26 + s);
          }
          if (s == 2 && TS0 <= 2 && c == 2 && lane == 0) red_relaxed(&g_flag[b * 8 + ((pi + s) & 3) * 2 + hf][3 + s]);
          if (s == 3 && c == 4) {
            mbar_wait(bar(B_FULLA), 1);
            uint4 pu[4];
#pragma unroll
            for (int i = 0; i < 4; i++) { pt[i] = lds128(sb + aslot(2) + 16384 + warp * 2048 + i * 512 + lane * 16); pu[i] = lds128(sb + aslot(2) + 32768 + warp * 2048 + i * 512 + lane * 16); }
            early_bad = stale<4>(pt, tag) | stale<4>(pu, tag);
#pragma unroll
            for (int i = 0; i < 4; i++) {
              const uint32_t w[4] = {pt[i].x, pt[i].y, pt[i].z, pt[i].w}, u[4] = {pu[i].x, pu[i].y, pu[i].z, pu[i].w};
#pragma unroll
              for (int e = 0; e < 4; e++) {
                const float rs = (e & 1) ? st1.y : st0.y, mu = (e & 1) ? st1.x : st0.x;
                const uint32_t hr = lds32(sb + aslot(2) + warp * 2048 + (e & 1) * 1024 + (2 * i + (e >> 1)) * 128 + lane * 4);
                sum[8 * i + 2 * e] = (bf_lo(w[e]) + bf_lo(u[e])) * rs + (bf_lo(hr) + mu);
                sum[8 * i + 2 * e + 1] = (bf_hi(w[e]) + bf_hi(u[e])) * rs + (bf_hi(hr) + mu);
              }
            }
            pin(sum);
          }
          if (s == 3 && c == 5) {
#pragma unroll
            for (int i = 0; i < 4; i++) pt[i] = ldg128_ll(psrc + 32768 + i * 512);
          }
        }
      }
      PROFT(0, 15);
      wg_wait<0>();
      pin(accQ);
      if (__builtin_expect(early_bad, 0)) {
        CNT(2);
#pragma unroll
        for (int i = 0; i < 16; i++) {
          const uint32_t hr = lds32(sb + aslot(2) + warp * 2048 + (i & 1) * 1024 + (i >> 1) * 128 + lane * 4);
          sum[2 * i] = bf_lo(hr) + ((i & 1) ? st1.x : st0.x); sum[2 * i + 1] = bf_hi(hr) + ((i & 1) ? st1.x : st0.x);
        }
      }
#pragma unroll 1
      for (int q = 2; q >= 0; q--) {
        for (int it = 0; (q < 2 && it == 0) || (stale<4>(pt, tag) && it < (1 << 17)); it++) {
          CNT(3);
#pragma unroll
          for (int i = 0; i < 4; i++) pt[i] = ldg128_ll(psrc + q * 16384 + i * 512);
        }
#pragma unroll
        for (int i = 0; i < 4; i++) {
          const float r0 = st0.y, r1 = st1.y;
          sum[8 * i] += bf_lo(pt[i].x) * r0; sum[8 * i + 1] += bf_hi(pt[i].x) * r0; sum[8 * i + 2] += bf_lo(pt[i].y) * r1; sum[8 * i + 3] += bf_hi(pt[i].y) * r1;
          sum[8 * i + 4] += bf_lo(pt[i].z) * r0; sum[8 * i + 5] += bf_hi(pt[i].z) * r0; sum[8 * i + 6] += bf_lo(pt[i].w) * r1; sum[8 * i + 7] += bf_hi(pt[i].w) * r1;
        }
        if (!early_bad) break;
      }
      __syncwarp();
      PROFT(0, 25);
      __nv_bfloat16* outp = p.out + (size_t)(b * 128 + warp * 16 + g) * DM + hf * 256 + pi * 64 + (q4 & 1) * 8 + (q4 >> 1) * 4;
      const bool odd = tid & 1;
#pragma unroll
      for (int i = 0; i < 8; i += 2) {
        uint32_t w[2][2];
#pragma unroll
        for (int e = 0; e < 2; e++) {
          const int x = 4 * (i + e);
          w[e][0] = pack_bf16(accQ[x] * st0.y + sum[x], accQ[x + 1] * st0.y + sum[x + 1]);
          w[e][1] = pack_bf16(accQ[x + 2] * st1.y + sum[x + 2], accQ[x + 3] * st1.y + sum[x + 3]);
        }
#pragma unroll
        for (int r = 0; r < 2; r++) {
          const uint32_t got = __shfl_xor_sync(0xffffffffu, odd ? w[0][r] : w[1][r], 1);
          stg64(outp + r * 8 * DM + i * 8, odd ? got : w[0][r], odd ? w[1][r] : got);
        }
      }
    }
    asm volatile("cp.async.bulk.wait_group 0;" ::: "memory");
    PROFT(0, 16);
  }
}
#undef lane
#undef g
#undef q4
#undef psrc

typedef CUresult (*EncodeFn)(CUtensorMap*, CUtensorMapDataType, cuuint32_t, void*, const cuuint64_t*, const cuuint64_t*, const cuuint32_t*,
                             const cuuint32_t*, CUtensorMapInterleave, CUtensorMapSwizzle, CUtensorMapL2promotion, CUtensorMapFloatOOBfill);

void make_map(EncodeFn enc, CUtensorMap* m, const void* ptr, int rank, uint64_t d0, uint64_t d1, uint64_t d2, uint64_t s1, uint64_t s2,
              uint32_t b0, uint32_t b1, uint32_t b2, CUtensorMapSwizzle sw) {
  cuuint64_t gd[3] = {d0, d1, d2};
  cuuint64_t gs[2] = {s1, s2};
  cuuint32_t bd[3] = {b0, b1, b2};
  cuuint32_t es[3] = {1, 1, 1};
  enc(m, CU_TENSOR_MAP_DATA_TYPE_BFLOAT16, rank, const_cast<void*>(ptr), gd, gs, bd, es, CU_TENSOR_MAP_INTERLEAVE_NONE, sw,
      CU_TENSOR_MAP_L2_PROMOTION_L2_128B, CU_TENSOR_MAP_FLOAT_OOB_FILL_NONE);
}

}

extern "C" void kernel_launch(void* const* d_in, const int* in_sizes, int n_in, void* d_out, int out_size) {
  (void)in_sizes; (void)n_in; (void)out_size;
  static EncodeFn enc = nullptr;
  if (!enc) {
    void* f = nullptr;
    cudaDriverEntryPointQueryResult qr;
    cudaGetDriverEntryPoint("cuTensorMapEncodeTiled", &f, cudaEnableDefault, &qr);
    enc = (EncodeFn)f;
    cudaFuncSetAttribute(fused_block_kernel, cudaFuncAttributeMaxDynamicSharedMemorySize, SMEM_TOTAL);
  }
  Params p;
  p.x = (const __nv_bfloat16*)d_in[0];
  p.wqkv = (const __nv_bfloat16*)d_in[1];
  p.wo = (const __nv_bfloat16*)d_in[2];
  p.wg = (const __nv_bfloat16*)d_in[4];
  p.wu = (const __nv_bfloat16*)d_in[5];
  p.wd = (const __nv_bfloat16*)d_in[6];
  p.out = (__nv_bfloat16*)d_out;
  make_map(enc, &p.tm_x, p.x, 2, DM, SEQ, 1, DM * 2, 0, 64, 128, 1, CU_TENSOR_MAP_SWIZZLE_128B);
  make_map(enc, &p.tm_qkv, p.wqkv, 2, 1536, 512, 1, 3072, 0, 64, 128, 1, CU_TENSOR_MAP_SWIZZLE_128B);
  {
    cuuint64_t gd[5] = {512, 2, 4, 4, 16};
    cuuint64_t gs[4] = {1024, 8 * 1024, 2 * 1024, 32 * 1024};
    cuuint32_t bd[5] = {64, 2, 4, 4, 8};
    cuuint32_t es[5] = {1, 1, 1, 1, 1};
    enc(&p.tm_wo, CU_TENSOR_MAP_DATA_TYPE_BFLOAT16, 5, const_cast<__nv_bfloat16*>(p.wo), gd, gs, bd, es, CU_TENSOR_MAP_INTERLEAVE_NONE,
        CU_TENSOR_MAP_SWIZZLE_128B, CU_TENSOR_MAP_L2_PROMOTION_L2_128B, CU_TENSOR_MAP_FLOAT_OOB_FILL_NONE);
  }
  make_map(enc, &p.tm_g1, p.wg, 2, FF, 512, 1, FF * 2, 0, 64, 128, 1, CU_TENSOR_MAP_SWIZZLE_128B);
  make_map(enc, &p.tm_u1, p.wu, 2, FF, 512, 1, FF * 2, 0, 64, 128, 1, CU_TENSOR_MAP_SWIZZLE_128B);
  make_map(enc, &p.tm_g2, p.wg, 3, FF, 512, 3, FF * 2, 64, 32, 64, 3, CU_TENSOR_MAP_SWIZZLE_64B);
  make_map(enc, &p.tm_u2, p.wu, 3, FF, 512, 3, FF * 2, 64, 32, 64, 3, CU_TENSOR_MAP_SWIZZLE_64B);
  make_map(enc, &p.tm_d, p.wd, 2, DM, FF, 1, DM * 2, 0, 64, 224, 1, CU_TENSOR_MAP_SWIZZLE_128B);
  fused_block_kernel<<<NCTA, 384, SMEM_TOTAL>>>(p);
}
```

```cpp
#include <cuda_runtime.h>
#include <cuda.h>
#include <cuda_bf16.h>
#include <stdint.h>

namespace {

constexpr int SEQ = 2048, DM = 512, FF = 1792;
constexpr int NCTA = 128;
constexpr float LN_EPS = 1e-5f;

constexpr uint32_t KB = 1024;
constexpr uint32_t SM_X = 0;
constexpr uint32_t SM_WQ = 0, SM_WV = 64 * KB, SM_WK = 128 * KB;
constexpr uint32_t SM_KV = 128 * KB;
__host__ __device__ constexpr uint32_t wopiece(int chunk, int khalf) { return (khalf ? 0u : 64 * KB) + chunk * 32 * KB; }
constexpr uint32_t SM_O = 128 * KB;
constexpr uint32_t SM_HE = 192 * KB;
constexpr uint32_t MISC = 229376;
constexpr uint32_t SM_BAR = MISC;
constexpr uint32_t SM_EPOCH = MISC + 248;
constexpr uint32_t SM_WB = MISC + 640;
constexpr uint32_t SMEM_TOTAL = 232448;
__host__ __device__ constexpr uint32_t cslot(int s) { return 64 * KB + ((s + 1) % 3) * 32 * KB; }
__host__ __device__ constexpr uint32_t aslot(int s) { return s < 2 ? 192 * KB - s * 32 * KB : (uint32_t)(s - 2) * 32 * KB; }

__host__ __device__ constexpr uint32_t cstage(int kp) {
  return kp == 2 ? 48 * KB : (kp == 0 || kp == 4 || kp == 7 ? 72 * KB : (kp == 1 || kp == 5 ? 96 * KB : 136 * KB));
}

constexpr int B_FULLA = 0;
constexpr int B_FULLW = 8;
constexpr int B_EMPTYA = 14;
constexpr int B_KV1 = 18, B_KV2 = 19;
constexpr int B_WO = 20;
constexpr int B_CDONE = 21;
constexpr int B_AUX = 22;
constexpr int B_FULLC = 23;
constexpr int B_EMPTYC = 26;
constexpr int B_RECV = 29;
constexpr int B_PEER = 30;

#define TS0 3
#define HPOS 1
#define NEARLY 3
#define AUNR_ 1
constexpr int AUNR = AUNR_;
#define FV 1
#define AV 1
#define XP0 1
#define XP1 3
#define KSP 3
#define VSP 1
constexpr int B_FULLS = 32;
constexpr int B_DONES = 41;
constexpr int B_OHALF = 50, B_ODONE = 51;
constexpr int B_X = 71;
constexpr int B_HP = 52, B_HV = 58;
constexpr int NB_CONS = 1, NB_RELKV = 2, NB_WG = 6, NB_RELH = 4, NB_RELS = 5;

__device__ __align__(128) uint8_t g_kv[NCTA][32768];
__device__ __align__(128) uint8_t g_o[NCTA][16384];
__device__ __align__(128) uint8_t g_h[NCTA][16384];
__device__ __align__(128) uint4 g_stat2[NCTA][64];
__device__ __align__(128) uint32_t g_wb[8][64];
__device__ __align__(128) uint2 g_om[NCTA][64];
__device__ __align__(128) uint8_t g_p[NCTA][3][16384];
__device__ unsigned g_flag[NCTA][32];
__device__ unsigned g_ticket[32];
#define CNT(i) do {} while (0)
#define PROF(i) do {} while (0)
#define PROFT(t, i) do {} while (0)

struct Params {
  CUtensorMap tm_x, tm_qkv, tm_wo, tm_g1, tm_u1, tm_g2, tm_u2, tm_d;
  const __nv_bfloat16 *x, *wqkv, *wo, *wg, *wu, *wd;
  __nv_bfloat16* out;
};

__device__ __forceinline__ void mbar_init(uint32_t b, uint32_t c) { asm volatile("mbarrier.init.shared::cta.b64 [%0], %1;" ::"r"(b), "r"(c) : "memory"); }
__device__ __forceinline__ void mbar_expect(uint32_t b, uint32_t bytes) { asm volatile("mbarrier.arrive.expect_tx.shared::cta.b64 _, [%0], %1;" ::"r"(b), "r"(bytes) : "memory"); }
__device__ __forceinline__ void mbar_arrive(uint32_t b) { asm volatile("mbarrier.arrive.shared::cta.b64 _, [%0];" ::"r"(b) : "memory"); }
__device__ __forceinline__ void mbar_arrive_remote(uint32_t rb) { asm volatile("mbarrier.arrive.relaxed.cluster.shared::cluster.b64 _, [%0];" ::"r"(rb) : "memory"); }
__device__ __forceinline__ bool elect_one() {
  uint32_t r;
  asm volatile("{ .reg .pred p; elect.sync _|p, 0xffffffff; selp.u32 %0, 1, 0, p; }" : "=r"(r));
  return r != 0;
}
__device__ __forceinline__ uint32_t mapa(uint32_t a, uint32_t cta) { uint32_t r; asm volatile("mapa.shared::cluster.u32 %0, %1, %2;" : "=r"(r) : "r"(a), "r"(cta)); return r; }
__device__ __forceinline__ void mbar_wait(uint32_t b, uint32_t ph) {
  asm volatile("{ .reg .pred p, q; .reg .u32 n; mov.u32 n, 0x20000;\n"
               "MW%=: add.u32 n, n, -1; setp.ne.u32 q, n, 0;\n"
               "mbarrier.try_wait.parity.shared::cta.b64 p, [%0], %1;\n"
               "not.pred p, p; and.pred p, p, q; @p bra MW%=; }" ::"r"(b), "r"(ph) : "memory");
}
__device__ __forceinline__ void tma2d(uint32_t dst, const CUtensorMap* m, int c0, int c1, uint32_t bar) {
  asm volatile("cp.async.bulk.tensor.2d.shared::cluster.global.mbarrier::complete_tx::bytes [%0], [%1, {%3, %4}], [%2];" ::"r"(dst), "l"(m), "r"(bar), "r"(c0), "r"(c1) : "memory");
}
__device__ __forceinline__ void tma2d_pair(uint32_t dst, const CUtensorMap* m, int c0, int c1, uint32_t bar) {
  asm volatile("cp.async.bulk.tensor.2d.shared::cluster.global.mbarrier::complete_tx::bytes.multicast::cluster [%0], [%1, {%3, %4}], [%2], %5;" ::"r"(dst), "l"(m), "r"(bar), "r"(c0), "r"(c1), "h"((uint16_t)3) : "memory");
}
__device__ __forceinline__ void tma3d(uint32_t dst, const CUtensorMap* m, int c0, int c1, int c2, uint32_t bar) {
  asm volatile("cp.async.bulk.tensor.3d.shared::cluster.global.mbarrier::complete_tx::bytes [%0], [%1, {%3, %4, %5}], [%2];" ::"r"(dst), "l"(m), "r"(bar), "r"(c0), "r"(c1), "r"(c2) : "memory");
}
__device__ __forceinline__ void tma5d(uint32_t dst, const CUtensorMap* m, int c0, int c4, uint32_t bar) {
  asm volatile("cp.async.bulk.tensor.5d.shared::cluster.global.mbarrier::complete_tx::bytes [%0], [%1, {%3, %5, %5, %5, %4}], [%2];" ::"r"(dst), "l"(m), "r"(bar), "r"(c0), "r"(c4), "r"(0) : "memory");
}
__device__ __forceinline__ uint32_t bsub2(uint32_t a, uint32_t b) { uint32_t r; asm("sub.rn.bf16x2 %0, %1, %2;" : "=r"(r) : "r"(a), "r"(b)); return r; }
__device__ __forceinline__ uint32_t bmul2(uint32_t a, uint32_t b) { uint32_t r; asm("mul.rn.bf16x2 %0, %1, %2;" : "=r"(r) : "r"(a), "r"(b)); return r; }
__device__ __forceinline__ void bulk_g2s(uint32_t dst, const void* src, uint32_t bytes, uint32_t bar) {
  asm volatile("cp.async.bulk.shared::cluster.global.mbarrier::complete_tx::bytes [%0], [%1], %2, [%3];" ::"r"(dst), "l"(src), "r"(bytes), "r"(bar) : "memory");
}
__device__ __forceinline__ void bulk_g2s_pair(uint32_t dst, const void* src, uint32_t bytes, uint32_t bar) {
  asm volatile("cp.async.bulk.shared::cluster.global.mbarrier::complete_tx::bytes.multicast::cluster [%0], [%1], %2, [%3], %4;" ::"r"(dst), "l"(src), "r"(bytes), "r"(bar), "h"((uint16_t)3) : "memory");
}
__device__ __forceinline__ void bulk_s2g(void* dst, uint32_t src, uint32_t bytes) {
  asm volatile("cp.async.bulk.global.shared::cta.bulk_group [%0], [%1], %2;" ::"l"(dst), "r"(src), "r"(bytes) : "memory");
  asm volatile("cp.async.bulk.commit_group;" ::: "memory");
}
__device__ __forceinline__ void bulk_prefetch(const void* src, uint32_t bytes) { asm volatile("cp.async.bulk.prefetch.L2.global [%0], %1;" ::"l"(src), "r"(bytes) : "memory"); }
__device__ __forceinline__ void prefetch_tm(const CUtensorMap* m) { asm volatile("prefetch.tensormap [%0];" ::"l"(m) : "memory"); }
__device__ __forceinline__ void nb_sync(int id, int n) { asm volatile("bar.sync %0, %1;" ::"r"(id), "r"(n) : "memory"); }
__device__ __forceinline__ void nb_arrive(int id, int n) { asm volatile("bar.arrive %0, %1;" ::"r"(id), "r"(n) : "memory"); }
__device__ __forceinline__ bool nb_any(int id, int n, bool v) {
  uint32_t r;
  asm volatile("{ .reg .pred p, q; setp.ne.u32 p, %1, 0; bar.red.or.pred q, %2, %3, p; selp.u32 %0, 1, 0, q; }" : "=r"(r) : "r"((uint32_t)v), "r"(id), "r"(n) : "memory");
  return r != 0;
}
__device__ __forceinline__ void red_release(unsigned* f) { asm volatile("red.release.gpu.global.add.u32 [%0], 1;" ::"l"(f) : "memory"); }
__device__ __forceinline__ void red_relaxed(unsigned* f) { asm volatile("red.relaxed.gpu.global.add.u32 [%0], 1;" ::"l"(f) : "memory"); }
__device__ __forceinline__ void poll_flag(const unsigned* f, unsigned target) {
  asm volatile("{ .reg .pred p; .reg .u32 n, v; mov.u32 n, 0x20000;\n"
               "PF%=: ld.relaxed.gpu.global.u32 v, [%0]; sub.u32 v, v, %1; setp.ge.s32 p, v, 0;\n"
               "@!p add.u32 n, n, -1; @!p setp.eq.u32 p, n, 0; @!p bra PF%=; }" ::"l"(f), "r"(target) : "memory");
}
__device__ __forceinline__ void red_lane0(unsigned* f, int lane_) {
  asm volatile("{ .reg .pred p; setp.eq.u32 p, %1, 0; @p red.relaxed.gpu.global.add.u32 [%0], 1; }" ::"l"(f + lane_), "r"(lane_) : "memory");
}
__device__ __forceinline__ void stg64_if(void* a, uint32_t x, uint32_t y, bool c) {
  asm volatile("{ .reg .pred p; setp.ne.u32 p, %3, 0; @p st.relaxed.gpu.global.v2.u32 [%0], {%1, %2}; }" ::"l"(a), "r"(x), "r"(y), "r"((uint32_t)c) : "memory");
}
__device__ __forceinline__ void stg128_if(void* a, uint32_t x, uint32_t y, uint32_t z, uint32_t w, bool c) {
  asm volatile("{ .reg .pred p; setp.ne.u32 p, %5, 0; @p st.relaxed.gpu.global.v4.u32 [%0], {%1, %2, %3, %4}; }" ::"l"(a), "r"(x), "r"(y), "r"(z), "r"(w), "r"((uint32_t)c) : "memory");
}
__device__ __forceinline__ void fence_async_global() { asm volatile("fence.proxy.async.global;" ::: "memory"); }
__device__ __forceinline__ void acquire_flag(const unsigned* f) { asm volatile("{ .reg .u32 v; ld.acquire.gpu.global.u32 v, [%0]; }" ::"l"(f) : "memory"); }
__device__ __forceinline__ void wg_fence() { asm volatile("wgmma.fence.sync.aligned;" ::: "memory"); }
__device__ __forceinline__ void wg_commit() { asm volatile("wgmma.commit_group.sync.aligned;" ::: "memory"); }
template <int N> __device__ __forceinline__ void wg_wait() { asm volatile("wgmma.wait_group.sync.aligned %0;" ::"n"(N) : "memory"); }
__device__ __forceinline__ uint64_t mkdesc(uint32_t addr, uint32_t lbo, uint32_t sbo, uint64_t sw) {
  return (uint64_t)((addr & 0x3FFFF) >> 4) | ((uint64_t)(lbo >> 4) << 16) | ((uint64_t)(sbo >> 4) << 32) | (sw << 62);
}
__device__ __forceinline__ uint32_t pack_bf16(float lo, float hi) { uint32_t r; asm("cvt.rn.bf16x2.f32 %0, %1, %2;" : "=r"(r) : "f"(hi), "f"(lo)); return r; }
__device__ __forceinline__ uint32_t pack_relu(float lo, float hi) { uint32_t r; asm("cvt.rn.relu.bf16x2.f32 %0, %1, %2;" : "=r"(r) : "f"(hi), "f"(lo)); return r; }
__device__ __forceinline__ float bf_lo(uint32_t v) { return __uint_as_float(v << 16); }
__device__ __forceinline__ float bf_hi(uint32_t v) { return __uint_as_float(v & 0xffff0000u); }
__device__ __forceinline__ float ex2(float x) { float r; asm("ex2.approx.ftz.f32 %0, %1;" : "=f"(r) : "f"(x)); return r; }
__device__ __forceinline__ void sts32(uint32_t a, uint32_t v) { asm volatile("st.shared.u32 [%0], %1;" ::"r"(a), "r"(v) : "memory"); }
__device__ __forceinline__ float2 lds64f(uint32_t a) { float2 v; asm volatile("ld.shared.v2.f32 {%0, %1}, [%2];" : "=f"(v.x), "=f"(v.y) : "r"(a) : "memory"); return v; }
__device__ __forceinline__ void sts64f(uint32_t a, float2 v) { asm volatile("st.shared.v2.f32 [%0], {%1, %2};" ::"r"(a), "f"(v.x), "f"(v.y) : "memory"); }
__device__ __forceinline__ void sts128f(uint32_t a, float4 v) { asm volatile("st.shared.v4.f32 [%0], {%1, %2, %3, %4};" ::"r"(a), "f"(v.x), "f"(v.y), "f"(v.z), "f"(v.w) : "memory"); }
__device__ __forceinline__ float4 lds128f(uint32_t a) { float4 v; asm volatile("ld.shared.v4.f32 {%0, %1, %2, %3}, [%4];" : "=f"(v.x), "=f"(v.y), "=f"(v.z), "=f"(v.w) : "r"(a) : "memory"); return v; }
__device__ __forceinline__ uint4 ldg128_nc(const void* p) { uint4 v; asm volatile("ld.global.nc.v4.u32 {%0, %1, %2, %3}, [%4];" : "=r"(v.x), "=r"(v.y), "=r"(v.z), "=r"(v.w) : "l"(p)); return v; }
__device__ __forceinline__ uint32_t ldg32_nc(const void* p) { uint32_t v; asm volatile("ld.global.nc.u32 %0, [%1];" : "=r"(v) : "l"(p)); return v; }
__device__ __forceinline__ uint32_t ldg32_cg(const void* p) { uint32_t v; asm volatile("ld.global.cg.u32 %0, [%1];" : "=r"(v) : "l"(p) : "memory"); return v; }
__device__ __forceinline__ float4 ldg128f_cg(const void* p) { float4 v; asm volatile("ld.global.cg.v4.f32 {%0, %1, %2, %3}, [%4];" : "=f"(v.x), "=f"(v.y), "=f"(v.z), "=f"(v.w) : "l"(p) : "memory"); return v; }
__device__ __forceinline__ float2 ldg64f_cg(const void* p) { float2 v; asm volatile("ld.global.cg.v2.f32 {%0, %1}, [%2];" : "=f"(v.x), "=f"(v.y) : "l"(p) : "memory"); return v; }
__device__ __forceinline__ void stg32(void* p, uint32_t v) { asm volatile("st.global.u32 [%0], %1;" ::"l"(p), "r"(v) : "memory"); }
__device__ __forceinline__ void stg128_ll(void* p, uint32_t a, uint32_t b, uint32_t c, uint32_t d) {
  asm volatile("st.relaxed.gpu.global.v4.u32 [%0], {%1, %2, %3, %4};" ::"l"(p), "r"(a), "r"(b), "r"(c), "r"(d) : "memory");
}
__device__ __forceinline__ void bulk_s2peer(uint32_t rdst, uint32_t src, uint32_t bytes, uint32_t rbar) {
  asm volatile("cp.async.bulk.shared::cluster.shared::cta.mbarrier::complete_tx::bytes [%0], [%1], %2, [%3];" ::"r"(rdst), "r"(src), "r"(bytes), "r"(rbar) : "memory");
}
__device__ __forceinline__ void stg128(void* p, uint4 v) { asm volatile("st.global.v4.u32 [%0], {%1, %2, %3, %4};" ::"l"(p), "r"(v.x), "r"(v.y), "r"(v.z), "r"(v.w) : "memory"); }
__device__ __forceinline__ void stg64(void* p, uint32_t a, uint32_t b) { asm volatile("st.global.v2.u32 [%0], {%1, %2};" ::"l"(p), "r"(a), "r"(b) : "memory"); }
__device__ __forceinline__ uint4 ldg128_ll(const void* p) {
  uint4 v;
  asm volatile("ld.relaxed.gpu.global.v4.u32 {%0, %1, %2, %3}, [%4];" : "=r"(v.x), "=r"(v.y), "=r"(v.z), "=r"(v.w) : "l"(p) : "memory");
  return v;
}
__device__ __forceinline__ uint2 ldg64_ll(const void* p) { uint2 v; asm volatile("ld.relaxed.gpu.global.v2.u32 {%0, %1}, [%2];" : "=r"(v.x), "=r"(v.y) : "l"(p) : "memory"); return v; }
__device__ __forceinline__ void stg64_ll(void* p, uint32_t a, uint32_t b) { asm volatile("st.relaxed.gpu.global.v2.u32 [%0], {%1, %2};" ::"l"(p), "r"(a), "r"(b) : "memory"); }
__device__ __forceinline__ void sts128(uint32_t a, uint4 v) { asm volatile("st.shared.v4.u32 [%0], {%1, %2, %3, %4};" ::"r"(a), "r"(v.x), "r"(v.y), "r"(v.z), "r"(v.w) : "memory"); }
__device__ __forceinline__ uint32_t lds32(uint32_t a) { uint32_t v; asm volatile("ld.shared.u32 %0, [%1];" : "=r"(v) : "r"(a) : "memory"); return v; }
__device__ __forceinline__ uint4 lds128(uint32_t a) { uint4 v; asm volatile("ld.shared.v4.u32 {%0, %1, %2, %3}, [%4];" : "=r"(v.x), "=r"(v.y), "=r"(v.z), "=r"(v.w) : "r"(a) : "memory"); return v; }
__device__ __forceinline__ void stg128f(void* p, const float* v) { asm volatile("st.global.v4.f32 [%0], {%1, %2, %3, %4};" ::"l"(p), "f"(v[0]), "f"(v[1]), "f"(v[2]), "f"(v[3]) : "memory"); }
__device__ __forceinline__ void st_async128(uint32_t rdst, const uint32_t* v, uint32_t rbar) {
  asm volatile("st.async.weak.shared::cluster.mbarrier::complete_tx::bytes.v4.b32 [%0], {%1, %2, %3, %4}, [%5];" ::"r"(rdst), "r"(v[0]), "r"(v[1]), "r"(v[2]), "r"(v[3]), "r"(rbar) : "memory");
}
__device__ __forceinline__ void fence_async_smem() { asm volatile("fence.proxy.async.shared::cta;" ::: "memory"); }
__device__ __forceinline__ uint32_t tagw(uint32_t v, uint32_t t, uint32_t m) { uint32_t r; asm("lop3.b32 %0, %1, %2, %3, 0xD8;" : "=r"(r) : "r"(v), "r"(t), "r"(m)); return r; }
template <int N> __device__ __forceinline__ uint32_t stale(const uint4* v, uint32_t tag) {
  uint32_t m = 0;
#pragma unroll
  for (int i = 0; i < N; i++) m |= v[i].x ^ tag;
  return m & 1;
}
template <int N> __device__ __forceinline__ uint32_t stale_smem(uint32_t addr, uint32_t stride, uint32_t tag) {
  uint32_t w[N], m0 = 0, m1 = 0;
#pragma unroll
  for (int i = 0; i < N; i++) w[i] = lds32(addr + i * stride);
#pragma unroll
  for (int i = 0; i < N; i += 2) { m0 |= w[i] ^ tag; m1 |= w[i + 1] ^ tag; }
  return (m0 | m1) & 1;
}
__device__ __forceinline__ void repair(uint32_t dst, const uint8_t* src, int n, uint32_t dstride, uint32_t sstride, uint32_t tag) {
  const int w = (threadIdx.x >> 3) & 3;
#pragma unroll 1
  for (int i = 0; i < n; i += 4) {
    uint4 v[4];
    uint32_t m;
    int it = 0;
    do {
      m = 0;
#pragma unroll
      for (int k = 0; k < 4; k++) v[k] = ldg128_ll(src + (size_t)(i + k) * sstride);
#pragma unroll
      for (int k = 0; k < 4; k++) m |= (w == 0 ? v[k].x : (w == 1 ? v[k].y : (w == 2 ? v[k].z : v[k].w))) ^ tag;
    } while ((m & 1) && ++it < (1 << 17));
#pragma unroll
    for (int k = 0; k < 4; k++) sts128(dst + (i + k) * dstride, v[k]);
  }
  fence_async_smem();
}
template <int N> __device__ __forceinline__ void pin(float (&d)[N]) {
#pragma unroll
  for (int i = 0; i < N; i++) asm volatile("" : "+f"(d[i])::"memory");
}
__device__ __forceinline__ void ldsm4(uint32_t a, uint32_t& r0, uint32_t& r1, uint32_t& r2, uint32_t& r3) {
  asm volatile("ldmatrix.sync.aligned.m8n8.x4.shared.b16 {%0, %1, %2, %3}, [%4];" : "=r"(r0), "=r"(r1), "=r"(r2), "=r"(r3) : "r"(a) : "memory");
}
__device__ __forceinline__ void ldsm4t(uint32_t a, uint32_t& r0, uint32_t& r1, uint32_t& r2, uint32_t& r3) {
  asm volatile("ldmatrix.sync.aligned.m8n8.x4.trans.shared.b16 {%0, %1, %2, %3}, [%4];" : "=r"(r0), "=r"(r1), "=r"(r2), "=r"(r3) : "r"(a) : "memory");
}
__device__ __forceinline__ void mma_acc(float (&c)[4], uint32_t a0, uint32_t a1, uint32_t a2, uint32_t a3, uint32_t b0, uint32_t b1) {
  asm("mma.sync.aligned.m16n8k16.row.col.f32.bf16.bf16.f32 {%0, %1, %2, %3}, {%4, %5, %6, %7}, {%8, %9}, {%0, %1, %2, %3};"
      : "+f"(c[0]), "+f"(c[1]), "+f"(c[2]), "+f"(c[3]) : "r"(a0), "r"(a1), "r"(a2), "r"(a3), "r"(b0), "r"(b1));
}
__device__ __forceinline__ void mma_k8(float (&c)[4], uint32_t a0, uint32_t a1, uint32_t b0) {
  asm("mma.sync.aligned.m16n8k8.row.col.f32.bf16.bf16.f32 {%0, %1, %2, %3}, {%4, %5}, {%6}, {%0, %1, %2, %3};"
      : "+f"(c[0]), "+f"(c[1]), "+f"(c[2]), "+f"(c[3]) : "r"(a0), "r"(a1), "r"(b0));
}
__device__ __forceinline__ void mma_zero(float* d, uint32_t a0, uint32_t a1, uint32_t a2, uint32_t a3, uint32_t b0, uint32_t b1) {
  asm("mma.sync.aligned.m16n8k16.row.col.f32.bf16.bf16.f32 {%0, %1, %2, %3}, {%4, %5, %6, %7}, {%8, %9}, {%10, %10, %10, %10};"
      : "=f"(d[0]), "=f"(d[1]), "=f"(d[2]), "=f"(d[3]) : "r"(a0), "r"(a1), "r"(a2), "r"(a3), "r"(b0), "r"(b1), "f"(0.f));
}

__device__ __forceinline__ void wgmma_rs_n64(float (&d)[32], uint32_t a0, uint32_t a1, uint32_t a2, uint32_t a3, uint64_t db, int sd) {
  asm volatile("{ .reg .pred p; setp.ne.b32 p, %37, 0;\n"
  "wgmma.mma_async.sync.aligned.m64n64k16.f32.bf16.bf16 {%0, %1, %2, %3, %4, %5, %6, %7, %8, %9, %10, %11, %12, %13, %14, %15, %16, %17, %18, %19, %20, %21, %22, %23, %24, %25, %26, %27, %28, %29, %30, %31}, {%32, %33, %34, %35}, %36, p, 1, 1, 1;\n}"
  : "+f"(d[0]), "+f"(d[1]), "+f"(d[2]), "+f"(d[3]), "+f"(d[4]), "+f"(d[5]), "+f"(d[6]), "+f"(d[7]), "+f"(d[8]), "+f"(d[9]), "+f"(d[10]), "+f"(d[11]), "+f"(d[12]), "+f"(d[13]), "+f"(d[14]), "+f"(d[15]), "+f"(d[16]), "+f"(d[17]), "+f"(d[18]), "+f"(d[19]), "+f"(d[20]), "+f"(d[21]), "+f"(d[22]), "+f"(d[23]), "+f"(d[24]), "+f"(d[25]), "+f"(d[26]), "+f"(d[27]), "+f"(d[28]), "+f"(d[29]), "+f"(d[30]), "+f"(d[31]) : "r"(a0), "r"(a1), "r"(a2), "r"(a3), "l"(db), "r"(sd));
}
__device__ __forceinline__ void wgmma_ss_n64(float (&d)[32], uint64_t da, uint64_t db, int sd) {
  asm volatile("{ .reg .pred p; setp.ne.b32 p, %34, 0;\n"
  "wgmma.mma_async.sync.aligned.m64n64k16.f32.bf16.bf16 {%0, %1, %2, %3, %4, %5, %6, %7, %8, %9, %10, %11, %12, %13, %14, %15, %16, %17, %18, %19, %20, %21, %22, %23, %24, %25, %26, %27, %28, %29, %30, %31}, %32, %33, p, 1, 1, 0, 1;\n}"
  : "+f"(d[0]), "+f"(d[1]), "+f"(d[2]), "+f"(d[3]), "+f"(d[4]), "+f"(d[5]), "+f"(d[6]), "+f"(d[7]), "+f"(d[8]), "+f"(d[9]), "+f"(d[10]), "+f"(d[11]), "+f"(d[12]), "+f"(d[13]), "+f"(d[14]), "+f"(d[15]), "+f"(d[16]), "+f"(d[17]), "+f"(d[18]), "+f"(d[19]), "+f"(d[20]), "+f"(d[21]), "+f"(d[22]), "+f"(d[23]), "+f"(d[24]), "+f"(d[25]), "+f"(d[26]), "+f"(d[27]), "+f"(d[28]), "+f"(d[29]), "+f"(d[30]), "+f"(d[31]) : "l"(da), "l"(db), "r"(sd));
}
__device__ __forceinline__ void wgmma_ss_n128(float (&d)[64], uint64_t da, uint64_t db, int sd) {
  asm volatile("{ .reg .pred p; setp.ne.b32 p, %66, 0;\n"
  "wgmma.mma_async.sync.aligned.m64n128k16.f32.bf16.bf16 {%0, %1, %2, %3, %4, %5, %6, %7, %8, %9, %10, %11, %12, %13, %14, %15, %16, %17, %18, %19, %20, %21, %22, %23, %24, %25, %26, %27, %28, %29, %30, %31, %32, %33, %34, %35, %36, %37, %38, %39, %40, %41, %42, %43, %44, %45, %46, %47, %48, %49, %50, %51, %52, %53, %54, %55, %56, %57, %58, %59, %60, %61, %62, %63}, %64, %65, p, 1, 1, 0, 1;\n}"
  : "+f"(d[0]), "+f"(d[1]), "+f"(d[2]), "+f"(d[3]), "+f"(d[4]), "+f"(d[5]), "+f"(d[6]), "+f"(d[7]), "+f"(d[8]), "+f"(d[9]), "+f"(d[10]), "+f"(d[11]), "+f"(d[12]), "+f"(d[13]), "+f"(d[14]), "+f"(d[15]), "+f"(d[16]), "+f"(d[17]), "+f"(d[18]), "+f"(d[19]), "+f"(d[20]), "+f"(d[21]), "+f"(d[22]), "+f"(d[23]), "+f"(d[24]), "+f"(d[25]), "+f"(d[26]), "+f"(d[27]), "+f"(d[28]), "+f"(d[29]), "+f"(d[30]), "+f"(d[31]), "+f"(d[32]), "+f"(d[33]), "+f"(d[34]), "+f"(d[35]), "+f"(d[36]), "+f"(d[37]), "+f"(d[38]), "+f"(d[39]), "+f"(d[40]), "+f"(d[41]), "+f"(d[42]), "+f"(d[43]), "+f"(d[44]), "+f"(d[45]), "+f"(d[46]), "+f"(d[47]), "+f"(d[48]), "+f"(d[49]), "+f"(d[50]), "+f"(d[51]), "+f"(d[52]), "+f"(d[53]), "+f"(d[54]), "+f"(d[55]), "+f"(d[56]), "+f"(d[57]), "+f"(d[58]), "+f"(d[59]), "+f"(d[60]), "+f"(d[61]), "+f"(d[62]), "+f"(d[63]) : "l"(da), "l"(db), "r"(sd));
}
__device__ __forceinline__ void wgmma_ss_n192(float (&d)[96], uint64_t da, uint64_t db, int sd) {
  asm volatile("{ .reg .pred p; setp.ne.b32 p, %98, 0;\n"
  "wgmma.mma_async.sync.aligned.m64n192k16.f32.bf16.bf16 {%0, %1, %2, %3, %4, %5, %6, %7, %8, %9, %10, %11, %12, %13, %14, %15, %16, %17, %18, %19, %20, %21, %22, %23, %24, %25, %26, %27, %28, %29, %30, %31, %32, %33, %34, %35, %36, %37, %38, %39, %40, %41, %42, %43, %44, %45, %46, %47, %48, %49, %50, %51, %52, %53, %54, %55, %56, %57, %58, %59, %60, %61, %62, %63, %64, %65, %66, %67, %68, %69, %70, %71, %72, %73, %74, %75, %76, %77, %78, %79, %80, %81, %82, %83, %84, %85, %86, %87, %88, %89, %90, %91, %92, %93, %94, %95}, %96, %97, p, 1, 1, 0, 1;\n}"
  : "+f"(d[0]), "+f"(d[1]), "+f"(d[2]), "+f"(d[3]), "+f"(d[4]), "+f"(d[5]), "+f"(d[6]), "+f"(d[7]), "+f"(d[8]), "+f"(d[9]), "+f"(d[10]), "+f"(d[11]), "+f"(d[12]), "+f"(d[13]), "+f"(d[14]), "+f"(d[15]), "+f"(d[16]), "+f"(d[17]), "+f"(d[18]), "+f"(d[19]), "+f"(d[20]), "+f"(d[21]), "+f"(d[22]), "+f"(d[23]), "+f"(d[24]), "+f"(d[25]), "+f"(d[26]), "+f"(d[27]), "+f"(d[28]), "+f"(d[29]), "+f"(d[30]), "+f"(d[31]), "+f"(d[32]), "+f"(d[33]), "+f"(d[34]), "+f"(d[35]), "+f"(d[36]), "+f"(d[37]), "+f"(d[38]), "+f"(d[39]), "+f"(d[40]), "+f"(d[41]), "+f"(d[42]), "+f"(d[43]), "+f"(d[44]), "+f"(d[45]), "+f"(d[46]), "+f"(d[47]), "+f"(d[48]), "+f"(d[49]), "+f"(d[50]), "+f"(d[51]), "+f"(d[52]), "+f"(d[53]), "+f"(d[54]), "+f"(d[55]), "+f"(d[56]), "+f"(d[57]), "+f"(d[58]), "+f"(d[59]), "+f"(d[60]), "+f"(d[61]), "+f"(d[62]), "+f"(d[63]), "+f"(d[64]), "+f"(d[65]), "+f"(d[66]), "+f"(d[67]), "+f"(d[68]), "+f"(d[69]), "+f"(d[70]), "+f"(d[71]), "+f"(d[72]), "+f"(d[73]), "+f"(d[74]), "+f"(d[75]), "+f"(d[76]), "+f"(d[77]), "+f"(d[78]), "+f"(d[79]), "+f"(d[80]), "+f"(d[81]), "+f"(d[82]), "+f"(d[83]), "+f"(d[84]), "+f"(d[85]), "+f"(d[86]), "+f"(d[87]), "+f"(d[88]), "+f"(d[89]), "+f"(d[90]), "+f"(d[91]), "+f"(d[92]), "+f"(d[93]), "+f"(d[94]), "+f"(d[95]) : "l"(da), "l"(db), "r"(sd));
}

__device__ __forceinline__ void mma_c4(float* d, const uint32_t (&q)[4], uint32_t b0, uint32_t b1, const float (&c)[4]) {
  asm("mma.sync.aligned.m16n8k16.row.col.f32.bf16.bf16.f32 {%0, %1, %2, %3}, {%4, %5, %6, %7}, {%8, %9}, {%10, %11, %12, %13};"
      : "=f"(d[0]), "=f"(d[1]), "=f"(d[2]), "=f"(d[3])
      : "r"(q[0]), "r"(q[1]), "r"(q[2]), "r"(q[3]), "r"(b0), "r"(b1), "f"(c[0]), "f"(c[1]), "f"(c[2]), "f"(c[3]));
}
__device__ __forceinline__ void sblock(float (&s)[8], const uint32_t (&q)[4], uint32_t ka, const float (&c)[4]) {
  uint32_t k0, k1, k2, k3;
  ldsm4(ka, k0, k1, k2, k3);
  mma_c4(&s[0], q, k0, k1, c);
  mma_c4(&s[4], q, k2, k3, c);
}
__device__ __forceinline__ void expack(const float (&s)[8], uint32_t (&p)[4]) {
  p[0] = pack_bf16(ex2(s[0]), ex2(s[1])); p[1] = pack_bf16(ex2(s[2]), ex2(s[3]));
  p[2] = pack_bf16(ex2(s[4]), ex2(s[5])); p[3] = pack_bf16(ex2(s[6]), ex2(s[7]));
}
__device__ __forceinline__ void pvblock(const uint32_t (&p)[4], uint32_t va, float (&o0)[4], float (&o1)[4], float (&l)[4]) {
  const uint32_t ONES = 0x3f803f80u;
  uint32_t v0, v1, v2, v3;
  ldsm4t(va, v0, v1, v2, v3);
  mma_acc(l, p[0], p[1], p[2], p[3], ONES, ONES);
  mma_acc(o0, p[0], p[1], p[2], p[3], v0, v1);
  mma_acc(o1, p[0], p[1], p[2], p[3], v2, v3);
}

__device__ __forceinline__ void attention(uint32_t sb, const uint32_t (&qf)[4][4], int b, int warp  , int lane, uint8_t* go, uint32_t& tag, unsigned* hint, float& pm0, float& pm1) {
  const int g = lane >> 2, q4 = lane & 3, mi = lane >> 3;
  const int tmin = max(0, 16 - 8 * b - warp), tl0 = max(1, tmin);
  const uint32_t kaddr = sb + SM_KV + (2 * warp + (mi >> 1)) * 2048 + (mi & 1) * 128 + (lane & 7) * 16;
  const uint32_t vaddr = sb + SM_KV + (2 * warp + (mi & 1)) * 2048 + (8 + (mi >> 1)) * 128 + (lane & 7) * 16;
  const bool pA = (2 * q4 <= g), pB = (2 * q4 + 1 <= g);
  const uint32_t mk = (pA ? 0x0000ffffu : 0u) | (pB ? 0xffff0000u : 0u);
  const uint32_t ONES = 0x3f803f80u;
  float o0[4][4], o1[4][4], l[4][4], c[4][4];
  const uint32_t zero = (b > 1000);
#pragma unroll
  for (int h = 0; h < 4; h++) {
    float d[4];
    uint32_t k0, k1, k2, k3;
    ldsm4(kaddr + h * 256 + 16 * 4096, k0, k1, k2, k3);
    mma_zero(d, qf[h][0], qf[h][1], qf[h][2], qf[h][3], k0, k1);
    c[h][0] = __shfl_sync(0xffffffffu, -d[0], lane & 28); c[h][2] = __shfl_sync(0xffffffffu, -d[2], lane & 28);
    c[h][1] = __shfl_sync(0xffffffffu, -d[0], 0, 4); c[h][3] = __shfl_sync(0xffffffffu, -d[2], 0, 4);
  }
#pragma unroll 1
  for (int attempt = 0; attempt < 2; attempt++) {
#pragma unroll
    for (int h = 0; h < 4; h++)
#pragma unroll
      for (int e = 0; e < 4; e++) { o0[h][e] = 0.f; o1[h][e] = 0.f; l[h][e] = 0.f; }
    float sc[8], pe[8];
    uint32_t pp[4];
#pragma unroll
    for (int e = 0; e < 8; e++) pe[e] = 0.f;
    if (warp == 0) mbar_wait(sb + SM_BAR + B_KV1 * 8, 0);
    sblock(sc, qf[0], kaddr + 15 * 4096, c[0]);
    uint32_t ka = kaddr + 15 * 4096, va = vaddr + 15 * 4096;
    int t = 15;
#pragma unroll 1
    for (int seg = 0; seg < 3; seg++) {
     if (seg >= 1) mbar_wait(sb + SM_BAR + (B_KV1 - 1 + seg) * 8, 0);
     const int tend = max(tl0, 17 - 8 * seg - warp);
#pragma unroll AUNR
     for (; t >= tend; t--) {
      float s1[8], s2[8], s3[8];
      uint32_t p[4];
#define PACKPE() pp[0] = pack_bf16(pe[0], pe[1]); pp[1] = pack_bf16(pe[2], pe[3]); pp[2] = pack_bf16(pe[4], pe[5]); pp[3] = pack_bf16(pe[6], pe[7])
      sblock(s1, qf[1], ka + 256, c[1]);
      PACKPE();
      pvblock(pp, va + 4096 + 768, o0[3], o1[3], l[3]);
      expack(sc, p);
      sblock(s2, qf[2], tagw(ka, p[0], zero) + 512, c[2]);
      pvblock(p, va, o0[0], o1[0], l[0]);
      expack(s1, p);
      sblock(s3, qf[3], tagw(ka, p[0], zero) + 768, c[3]);
      pvblock(p, va + 256, o0[1], o1[1], l[1]);
      expack(s2, p);
      sblock(sc, qf[0], tagw(ka, p[0], zero) - 4096, c[0]);
      pvblock(p, va + 512, o0[2], o1[2], l[2]);
#pragma unroll
      for (int e = 0; e < 8; e++) pe[e] = ex2(s3[e]);
      ka -= 4096; va -= 4096;
     }
    }
    pp[0] = pack_bf16(pe[0], pe[1]); pp[1] = pack_bf16(pe[2], pe[3]); pp[2] = pack_bf16(pe[4], pe[5]); pp[3] = pack_bf16(pe[6], pe[7]);
    pvblock(pp, va + 4096 + 768, o0[3], o1[3], l[3]);
    if (attempt == 0 && lane == 0) mbar_arrive(sb + SM_BAR + B_CDONE * 8);
    tag = __shfl_sync(0xffffffffu, lds32(sb + SM_EPOCH) + 1, 0);
    bool ok = true;
    uint32_t dep[4];
#pragma unroll
    for (int h = 0; h < 4; h++) {
      float d[8], tl[8];
      const uint32_t kf = (FV >= 1 && h >= 2) ? tagw(kaddr, dep[h - 2], zero) : kaddr;
      sblock(d, qf[h], kf + h * 256 + 16 * 4096, c[h]);
      if (FV >= 2 && h == 0) {
#pragma unroll
        for (int e = 0; e < 8; e++) tl[e] = sc[e];
      } else {
        sblock(tl, qf[h], kf + h * 256, c[h]);
      }
      if (tmin > 0) {
#pragma unroll
        for (int e = 0; e < 8; e++) tl[e] = -INFINITY;
      }
      const uint32_t p0 = pack_bf16(ex2(pA ? d[0] : tl[0]), ex2(pB ? d[1] : tl[1])), p1 = pack_bf16(ex2(d[2]), ex2(d[3]));
      const uint32_t p2 = pack_bf16(ex2(tl[4]), ex2(tl[5])), p3 = pack_bf16(ex2(pA ? d[6] : tl[6]), ex2(pB ? d[7] : tl[7]));
      dep[h] = (FV == 3) ? (p0 ^ p3) : p0;
      mma_acc(l[h], p0, p1, p2, p3, ONES, ONES);
      uint32_t v0, v1, v2, v3;
      ldsm4t(vaddr + h * 256 + 16 * 4096, v0, v1, v2, v3);
      mma_acc(o0[h], p0 & mk, p1, 0u, p3 & mk, v0, v1); mma_acc(o1[h], p0 & mk, p1, 0u, p3 & mk, v2, v3);
      ldsm4t(vaddr + h * 256, v0, v1, v2, v3);
      mma_acc(o0[h], p0 & ~mk, 0u, p2, p3 & ~mk, v0, v1); mma_acc(o1[h], p0 & ~mk, 0u, p2, p3 & ~mk, v2, v3);
    }
    ok = ((l[0][0] + l[0][2]) + (l[1][0] + l[1][2])) + ((l[2][0] + l[2][2]) + (l[3][0] + l[3][2])) <= 1.0e9f;
    if (__builtin_expect(attempt == 1 || __all_sync(0xffffffffu, ok), 1)) break;
    const float z[4] = {0.f, 0.f, 0.f, 0.f};
#pragma unroll
    for (int h = 0; h < 4; h++) { c[h][0] = -INFINITY; c[h][2] = -INFINITY; }
#pragma unroll 1
    for (int t = 16; t >= tmin; t--) {
      const bool a = (t == 16) ? pA : (t != 0 || !pA), bb = (t == 16) ? pB : (t != 0 || !pB);
#pragma unroll
      for (int h = 0; h < 4; h++) {
        float d[8];
        sblock(d, qf[h], kaddr + h * 256 + t * 4096, z);
        if (a) { c[h][0] = fmaxf(c[h][0], d[0]); c[h][2] = fmaxf(c[h][2], d[6]); }
        if (bb) { c[h][0] = fmaxf(c[h][0], d[1]); c[h][2] = fmaxf(c[h][2], d[7]); }
        if (t != 0) c[h][2] = fmaxf(c[h][2], fmaxf(d[2], d[3]));
        if (t != 16) c[h][0] = fmaxf(c[h][0], fmaxf(d[4], d[5]));
      }
    }
#pragma unroll
    for (int h = 0; h < 4; h++) {
      float m0 = c[h][0], m1 = c[h][2];
      m0 = fmaxf(m0, __shfl_xor_sync(0xffffffffu, m0, 1)); m1 = fmaxf(m1, __shfl_xor_sync(0xffffffffu, m1, 1));
      m0 = fmaxf(m0, __shfl_xor_sync(0xffffffffu, m0, 2)); m1 = fmaxf(m1, __shfl_xor_sync(0xffffffffu, m1, 2));
      c[h][0] = -m0; c[h][1] = -m0; c[h][2] = -m1; c[h][3] = -m1;
    }
  }
#pragma unroll
  for (int h = 0; h < 4; h++) {
    float i0, i1;
    asm("rcp.approx.ftz.f32 %0, %1;" : "=f"(i0) : "f"(l[h][0]));
    asm("rcp.approx.ftz.f32 %0, %1;" : "=f"(i1) : "f"(l[h][2]));
    o0[h][0] *= i0; o0[h][1] *= i0; o1[h][0] *= i0; o1[h][1] *= i0;
    o0[h][2] *= i1; o0[h][3] *= i1; o1[h][2] *= i1; o1[h][3] *= i1;
  }
  const uint32_t t0 = q4 == 0, t1 = q4 == 1, t2 = q4 == 2, t3 = q4 == 3;
#pragma unroll
  for (int h = 0; h < 4; h += 2) {
    stg128_ll(go + h * 256, tagw(pack_bf16(o0[h][0], o0[h][1]), tag, t0), tagw(pack_bf16(o1[h][0], o1[h][1]), tag, t1),
              tagw(pack_bf16(o0[h + 1][0], o0[h + 1][1]), tag, t2), tagw(pack_bf16(o1[h + 1][0], o1[h + 1][1]), tag, t3));
    stg128_ll(go + h * 256 + 1024, tagw(pack_bf16(o0[h][2], o0[h][3]), tag, t0), tagw(pack_bf16(o1[h][2], o1[h][3]), tag, t1),
              tagw(pack_bf16(o0[h + 1][2], o0[h + 1][3]), tag, t2), tagw(pack_bf16(o1[h + 1][2], o1[h + 1][3]), tag, t3));
  }
  __syncwarp();
  red_lane0(hint, lane);
  mbar_wait(sb + SM_BAR + B_AUX * 8, 0);
  float a0 = 0.f, a1 = 0.f;
#pragma unroll
  for (int h = 0; h < 4; h++) {
    const float2 u = lds64f(sb + SM_WB + (h * 16 + q4 * 2) * 4), v = lds64f(sb + SM_WB + (h * 16 + 8 + q4 * 2) * 4);
    a0 += o0[h][0] * u.x + o0[h][1] * u.y + o1[h][0] * v.x + o1[h][1] * v.y;
    a1 += o0[h][2] * u.x + o0[h][3] * u.y + o1[h][2] * v.x + o1[h][3] * v.y;
  }
  a0 += __shfl_xor_sync(0xffffffffu, a0, 1); a1 += __shfl_xor_sync(0xffffffffu, a1, 1);
  a0 += __shfl_xor_sync(0xffffffffu, a0, 2); a1 += __shfl_xor_sync(0xffffffffu, a1, 2);
  pm0 += a0; pm1 += a1;
}

__device__ __forceinline__ void reglu_block(const float* ag, const float* au, uint32_t& lo, uint32_t& hi) {
  lo = bmul2(pack_relu(ag[0], ag[1]), pack_bf16(au[0], au[1]));
  hi = bmul2(pack_relu(ag[2], ag[3]), pack_bf16(au[2], au[3]));
}

__global__ void __launch_bounds__(384, 1) __cluster_dims__(2, 1, 1) fused_block_kernel(const __grid_constant__ Params p) {
  extern __shared__ __align__(1024) uint8_t smem[];
  uint32_t sb = (uint32_t)__cvta_generic_to_shared(smem);
#define NEW_PHASE() asm volatile("mov.u32 %1, %%tid.x;" : "+r"(sb), "=r"(tid))
  int tid = threadIdx.x;
  const int warp = __shfl_sync(0xffffffffu, tid >> 5, 0);
#define lane (tid & 31)
#define g ((tid & 31) >> 2)
#define q4 (tid & 3)
  const int cta = blockIdx.x, b = cta >> 3, j = cta & 7;
  const int kb0 = j & 6;
  const int hf = j & 1, pi = j >> 1;
  auto bar = [&](int i) { return sb + SM_BAR + i * 8; };

  auto opaque = [](int v) { asm volatile("" : "+r"(v)); return v; };
  if (opaque(warp >> 3)) {
    asm volatile("setmaxnreg.dec.sync.aligned.u32 40;");
    if (opaque(warp == 8)) {
      if (lane == 0) PROF(0);
      if (elect_one()) {
        mbar_init(bar(B_X), 1); mbar_init(bar(B_X + 1), 1);
        fence_async_smem();
        mbar_expect(bar(B_X), 16384);
        tma2d(sb + SM_X, &p.tm_x, 0, b * 128, bar(B_X));
        mbar_expect(bar(B_X + 1), 16384);
        tma2d(sb + SM_X + 16384, &p.tm_x, 64, b * 128, bar(B_X + 1));
#pragma unroll
        for (int i = 2; i < 8; i++) mbar_init(bar(B_X + i), 1);
#pragma unroll
        for (int i = 0; i < 31; i++) if (i == 0 || i > 3) mbar_init(bar(i), ((0x5C23C000u >> i) & 1) ? 8 : 1);
        asm volatile("fence.mbarrier_init.release.cluster;" ::: "memory");
        fence_async_smem();
      }
      __syncwarp();
      nb_arrive(0, 384);
      asm volatile("barrier.cluster.arrive.relaxed.aligned;" ::: "memory");
      unsigned epoch = 0;
      if (elect_one()) {
#pragma unroll
        for (int i = 2; i < 8; i++) {
          mbar_expect(bar(B_X + i), 16384);
          tma2d(sb + SM_X + i * 16384, &p.tm_x, i * 64, b * 128, bar(B_X + i));
        }
#pragma unroll
        for (int c = 0; c < 12; c++) {
          if (c == 4) {
            mbar_expect(bar(B_RECV), 16384);
            bulk_prefetch((const uint8_t*)p.wqkv + cta * 12288, 12288);
            mbar_wait(bar(B_CDONE), 0);
          }
          if (c == 0 && 0 >= 0) { prefetch_tm(&p.tm_qkv); mbar_wait(bar(B_X + XP0), 0); }
          if (c == 1) mbar_wait(bar(B_X + XP1), 0);
          if (c == 8) mbar_wait(bar(B_FULLW + 2), 0);
          const uint32_t fb = bar(B_FULLW + (c == 1 ? 1 : c >> 1));
          if (c < 2 || (c >= 4 && (c & 1) == 0)) mbar_expect(fb, c == 0 ? 16384 : (c == 1 ? 49152 : 32768));
          tma2d(sb + SM_WK - (c >> 2) * 65536 + (c & 3) * 16384, &p.tm_qkv, (c < 8 ? 512 + (c >> 2) * 512 : 0) + j * 64, (c & 3) * 128, fb);
        }
        epoch = atomicAdd(&g_ticket[0], 1u) / NCTA;
        sts32(sb + SM_EPOCH, epoch);
        bulk_prefetch((const uint8_t*)p.wo + cta * 4096, 4096);
#pragma unroll
        for (int i = 0; i < 6; i++) prefetch_tm(&p.tm_wo + i);
        mbar_wait(bar(B_CDONE), 1);
      }
      __syncwarp();
      epoch = lds32(sb + SM_EPOCH);
      if (elect_one()) {
#pragma unroll
        for (int i = 0; i < 2; i++)
          if (b <= i) {
            mbar_arrive(bar(B_KV1 + i));
          } else {
            mbar_expect(bar(B_KV1 + i), 32768);
            if (i == 1) mbar_wait(bar(B_KV1), 0);
            poll_flag(&g_flag[cta - 8 - 8 * i][0], epoch + 1);
            fence_async_global();
            bulk_g2s(sb + SM_KV + (1 - i) * 32768, g_kv[cta - 8 - 8 * i], 32768, bar(B_KV1 + i));
          }
        mbar_expect(bar(B_WO), 131072);
        mbar_wait(bar(B_CDONE), 0);
        mbar_wait(bar(B_KV1), 0);
        mbar_wait(bar(B_KV2), 0);
#pragma unroll
        for (int c = 0; c < 4; c++) tma5d(sb + wopiece(c >> 1, c & 1), &p.tm_wo, kb0 * 64 + (c >> 1) * 64, (c & 1) * 8, bar(B_WO));
        bulk_prefetch((const uint8_t*)p.wg + cta * 14336, 14336);
        bulk_prefetch((const uint8_t*)p.wu + cta * 14336, 14336);
        bulk_prefetch((const uint8_t*)p.wd + cta * 14336, 14336);
#pragma unroll
        for (int c = 0; c < 4; c++) mbar_expect(bar(B_FULLA + 4 + c), 16384);
      }
      __syncwarp();
      mbar_wait(bar(B_CDONE), 1);
      if (lane < 8) poll_flag(&g_flag[b * 8 + lane][1], 8 * (epoch + 1));
      __syncwarp();
      if (elect_one()) {
        const uint8_t* src = g_o[b * 8] + hf * 8192;
#pragma unroll
        for (int c = 0; c < 8; c++) { if (c == 4) mbar_wait(bar(B_FULLA + 4), 0); bulk_g2s(sb + SM_O + c * 8192, src + c * 16384, 8192, bar(B_FULLA + 4 + (c >> 1))); }
        PROF(23);
        int sl = 0;
#pragma unroll
        for (int n = 0; n < 16; n++) {
          if (n < 12) mbar_wait(bar(n < 4 ? (n < NEARLY ? B_OHALF : B_ODONE) : B_DONES + (n < 7 ? n - 4 : n - 3)), 0);
          else mbar_wait(bar(B_EMPTYC + sl), n == 15);
          const uint32_t d = sb + (n == 0 ? cslot(1) : (n < 9 ? cstage(n - 1) : cslot(sl)));
          const uint32_t fb = bar(n < 9 ? B_FULLS + n : B_FULLC + sl);
          if (n < 9 && n != 0) {
            const int k0 = ((kb0 + n - 1) & 7) * 64;
            mbar_expect(fb, 24576);
            tma3d(d, &p.tm_g2, j * 224 + (hf ? 0 : 128), k0, 0, fb);
            tma3d(d + 12288, &p.tm_u2, j * 224 + (hf ? 0 : 128), k0, 0, fb);
          } else {
            const int k0 = ((kb0 + 2 * n) & 7) * 64, c0 = j * 224 + hf * 96 + (n >= 12 ? 64 : 0);
            mbar_expect(fb, 32768);
            tma2d(d, &p.tm_g1, c0, k0, fb);
            tma2d(d + 16384, &p.tm_u1, c0, k0, fb);
          }
          sl = (sl == 2) ? 0 : sl + 1;
        }
#pragma unroll
        for (int u = 0; u < 8; u++) {
          const uint32_t d = sb + ((0x45631204u >> (4 * u)) & 15) * 32768;
          const uint32_t fb = bar(8 + ((0x1001000f03110210ull >> (8 * u)) & 255));
          mbar_wait(bar(14 + ((0xD10C3E2Du >> (4 * u)) & 15)), (0x65u >> u) & 1);
          mbar_expect(fb, 28672);
          tma2d(d, &p.tm_d, hf * 256 + ((pi + 1 + (u >> 1)) & 3) * 64, (j ^ (u & 1)) * 224, fb);
        }
        const uint8_t* ps = g_p[cta][0];
        mbar_expect(bar(B_FULLA), 49152);
        mbar_wait(bar(B_EMPTYA + 2), 1);
        bulk_g2s(sb + aslot(2), g_h[b * 8 + hf * 4 + pi], 16384, bar(B_FULLA));
        poll_flag(&g_flag[cta][4], 8 * (epoch + 1));
        bulk_g2s(sb + aslot(2) + 16384, ps, 16384, bar(B_FULLA));
        mbar_wait(bar(B_EMPTYA + 3), 1);
        poll_flag(&g_flag[cta][5], 8 * (epoch + 1));
        bulk_g2s(sb + aslot(2) + 32768, ps + 16384, 16384, bar(B_FULLA));
      }
    } else {
      const int hw = warp - 9;
      if (hw == 0 && elect_one()) {
#pragma unroll
        for (int i = 32; i < 70; i++) mbar_init(bar(i), (i < B_DONES || i >= B_HP) ? 1 : (i == B_DONES + 3 ? 16 : 8));
        asm volatile("fence.mbarrier_init.release.cluster;" ::: "memory");
        fence_async_smem();
#pragma unroll
        for (int i = 0; i < 6; i++) mbar_expect(bar(B_HP + i), 16384);
      }
      __syncwarp();
      asm volatile("barrier.cluster.arrive.relaxed.aligned;" ::: "memory");
      nb_sync(0, 384);
      mbar_wait(bar(B_FULLW + 5), 0);
      if (opaque(hw == 0)) {
        nb_sync(NB_RELKV, 256 + 32);
        if (lane == 0) red_release(&g_flag[cta][0]);
        mbar_wait(bar(B_ODONE), 0);
        const unsigned epoch = lds32(sb + SM_EPOCH);
        if (lane < 8) poll_flag(&g_flag[b * 8 + lane][2], 8 * (epoch + 1));
        __syncwarp();
        if (elect_one()) {
          PROF(22);
#pragma unroll
          for (int kp = 2; kp < 8; kp++) {
            if (kp >= 4) mbar_wait(bar(B_HP + kp - 4), 0);
            if (kp == 7) mbar_wait(bar(B_DONES + 3), 0);
            bulk_g2s_pair(sb + aslot(kp >> 1) + (kp & 1) * 16384 + hf * 8192, g_h[b * 8 + ((kb0 + kp) & 7)] + hf * 8192, 8192, bar(B_HP + kp - 2));
          }
        }
        if (elect_one()) { mbar_wait(bar(B_RECV), 0); mbar_expect(bar(B_RECV), 40960); mbar_expect(bar(B_WO), 16384); }
      } else {
        const int h2 = hw - 1;
        const int wr = b * 4 + h2 * 2 + (lane >> 4);
        float ws = 0.f;
        {
          const __nv_bfloat16* src = p.wo + (size_t)(j * 64 + wr) * DM + (lane & 15) * 8;
          uint4 v[4];
#pragma unroll
          for (int r = 0; r < 4; r++) v[r] = ldg128_nc(src + r * 128);
#pragma unroll
          for (int r = 0; r < 4; r++)
            ws += (bf_lo(v[r].x) + bf_hi(v[r].x)) + (bf_lo(v[r].y) + bf_hi(v[r].y)) + (bf_lo(v[r].z) + bf_hi(v[r].z)) + (bf_lo(v[r].w) + bf_hi(v[r].w));
#pragma unroll
          for (int o = 8; o > 0; o >>= 1) ws += __shfl_xor_sync(0xffffffffu, ws, o);
        }
        mbar_wait(bar(B_KV1), 0);
        const unsigned epoch = lds32(sb + SM_EPOCH);
        if ((lane & 15) == 0)
          asm volatile("st.relaxed.gpu.global.u32 [%0], %1;" ::"l"(&g_wb[j][wr]), "r"(tagw(__float_as_uint(ws * (1.f / DM)), epoch + 1, 1)) : "memory");
        if (h2 == 0) {
          uint2 w;
          int it = 0;
          do { __nanosleep(400); w = ldg64_ll(&g_wb[j][lane * 2]); } while ((((w.x ^ (epoch + 1)) | (w.y ^ (epoch + 1))) & 1) && ++it < (1 << 16));
          sts64f(sb + SM_WB + lane * 8, make_float2(__uint_as_float(w.x), __uint_as_float(w.y)));
          __syncwarp();
          if (lane == 0) { mbar_arrive(bar(B_AUX)); PROF(19); }
        }
#pragma unroll 1
        for (int kp = 2; kp < 8; kp++) {
          const uint32_t hs = sb + aslot(kp >> 1) + (kp & 1) * 16384 + h2 * 8192 + lane * 16;
          mbar_wait(bar(B_HP + kp - 2), 0);
          if (__builtin_expect(stale_smem<16>(hs + (lane >> 3) * 4, 512, epoch + 1) != 0, 0)) {
            CNT(1);
            repair(hs, g_h[b * 8 + ((kb0 + kp) & 7)] + h2 * 8192 + lane * 16, 16, 512, 512, epoch + 1);
          }
          __syncwarp();
          if (lane == 0) mbar_arrive(bar(B_HV + 2 * (kp - 2) + h2));
        }
      }
    }
    __syncwarp();
    asm volatile("barrier.cluster.wait.acquire.aligned;" ::: "memory");
  } else {
    asm volatile("barrier.cluster.arrive.relaxed.aligned;" ::: "memory");
    asm volatile("setmaxnreg.inc.sync.aligned.u32 232;");
    const int wg = warp >> 2;
    const uint32_t peer = (uint32_t)(hf ^ 1);
    const uint32_t ONES = 0x3f803f80u;
    const int tile = wg ? 11 - warp : warp;
    nb_sync(0, 384);
    uint32_t qf[4][4];
    float pm0, pm1;
    {
      uint32_t xa[32][4];
      float rs0, rs1;
      float accX[32], accY[32];
      {
        float sa[2][4] = {}, va[2][4] = {}, vb[2][4] = {};
        const uint32_t xrow = sb + SM_X + (tile * 16 + (lane & 15)) * 128;
#pragma unroll
        for (int k8 = 0; k8 < 32; k8 += 4) {
          mbar_wait(bar(B_X + (k8 >> 2)), 0);
          if (k8 == 0) PROFT(0, 17);
#pragma unroll
          for (int k = k8; k < k8 + 4; k++) {
            ldsm4(xrow + (k >> 2) * 16384 + ((((k & 3) * 2 + (lane >> 4)) ^ (lane & 7)) << 4), xa[k][0], xa[k][1], xa[k][2], xa[k][3]);
          }
          if (k8 == 28) { __syncwarp(); if (lane == 0) mbar_arrive(bar(B_CDONE)); }
#pragma unroll
          for (int k = k8; k < k8 + 4; k++) {
            mma_acc(sa[k & 1], xa[k][0], xa[k][1], xa[k][2], xa[k][3], ONES, ONES);
            mma_k8(va[0], xa[k][0], xa[k][1], xa[k][0]); mma_k8(vb[0], xa[k][0], xa[k][1], xa[k][1]);
            mma_k8(va[1], xa[k][2], xa[k][3], xa[k][2]); mma_k8(vb[1], xa[k][2], xa[k][3], xa[k][3]);
          }
        }
        const float mean0 = (sa[0][0] + sa[1][0]) * (1.f / DM), mean1 = (sa[0][2] + sa[1][2]) * (1.f / DM);
        const uint32_t h0 = pack_bf16(mean0, mean0), h1 = pack_bf16(mean1, mean1);
        pm0 = mean0 * 0.125f; pm1 = mean1 * 0.125f;
        const float e0 = __shfl_sync(0xffffffffu, (g & 1) ? va[0][1] + va[1][1] : va[0][0] + va[1][0], (lane & 28) + (g >> 1));
        const float e1 = __shfl_sync(0xffffffffu, (g & 1) ? vb[0][3] + vb[1][3] : vb[0][2] + vb[1][2], (lane & 28) + (g >> 1));
        rs0 = rsqrtf(fmaxf(e0 * (1.f / DM) - mean0 * mean0, 0.f) + LN_EPS);
        rs1 = rsqrtf(fmaxf(e1 * (1.f / DM) - mean1 * mean1, 0.f) + LN_EPS);
        PROFT(0, 1);
        const uint64_t db = mkdesc(sb + SM_WK, 8192, 1024, 1);
#pragma unroll
        for (int kb = 0; kb < 8; kb++) {
#pragma unroll
          for (int k = 4 * kb; k < 4 * kb + 4; k++) {
            xa[k][0] = bsub2(xa[k][0], h0); xa[k][1] = bsub2(xa[k][1], h1); xa[k][2] = bsub2(xa[k][2], h0); xa[k][3] = bsub2(xa[k][3], h1);
          }
          mbar_wait(bar(B_FULLW + (kb >= 2)), 0);
          wg_fence();
#pragma unroll
          for (int k = 4 * kb; k < 4 * kb + 4; k++) wgmma_rs_n64(accX, xa[k][0], xa[k][1], xa[k][2], xa[k][3], db + k * 128, k != 0);
        }
        wg_commit();
      }
      NEW_PHASE();
      uint8_t* gkv = g_kv[cta] + tile * 4096 + lane * 4;
      const uint32_t skv = sb + SM_KV + 65536 + tile * 4096 + lane * 4;
#pragma unroll
      for (int ps = 0; ps < 2; ps++) {
        const uint64_t db = mkdesc(sb + (ps == 0 ? SM_WV : SM_WQ), 8192, 1024, 1);
#pragma unroll
        for (int k = 0; k < 32; k++) {
          if ((k & 15) == 0) { mbar_wait(bar(B_FULLW + 2 + ps * 2 + (k >> 4)), 0); wg_fence(); }
          if (ps == 0) wgmma_rs_n64(accY, xa[k][0], xa[k][1], xa[k][2], xa[k][3], db + k * 128, k != 0);
          else wgmma_rs_n64(accX, xa[k][0], xa[k][1], xa[k][2], xa[k][3], db + k * 128, k != 0);
          if (k == 2) {
            wg_commit();
            wg_wait<1>();
            if (ps == 0) { pin(accX); if (lane == 0) mbar_arrive(bar(B_CDONE)); PROFT(0, 2); } else { pin(accY); PROFT(0, 3); }
            wg_fence();
          }
          const int sp = (ps == 0) ? KSP : VSP;
          if (k >= 2 && (k - 2) % sp == 0 && (k - 2) / sp < 8) {
            const float* a = (ps == 0) ? accX : accY;
            const int i = (k - 2) / sp;
            const uint32_t lo = pack_bf16(rs0 * a[4 * i], rs0 * a[4 * i + 1]), hi = pack_bf16(rs1 * a[4 * i + 2], rs1 * a[4 * i + 3]);
            stg32(gkv + (ps * 8 + i) * 128, lo); stg32(gkv + 2048 + (ps * 8 + i) * 128, hi);
            sts32(skv + (ps * 8 + i) * 128, lo); sts32(skv + 2048 + (ps * 8 + i) * 128, hi);
            if (ps == 1 && i == 7) nb_arrive(NB_RELKV, 256 + 32);
          }
        }
        wg_commit();
      }
      wg_wait<0>();
      pin(accX);
      if (lane == 0) mbar_arrive(bar(B_CDONE));
      nb_sync(NB_CONS, 256);
      const float QS = 0.25f * 1.4426950408889634f;
      const float r0 = rs0 * QS, r1 = rs1 * QS;
#pragma unroll
      for (int i = 0; i < 8; i++) {
        qf[i >> 1][(i & 1) * 2] = pack_bf16(r0 * accX[4 * i], r0 * accX[4 * i + 1]);
        qf[i >> 1][(i & 1) * 2 + 1] = pack_bf16(r1 * accX[4 * i + 2], r1 * accX[4 * i + 3]);
      }
    }
    NEW_PHASE();
    PROFT(0, 5);
    uint32_t tag;
    const int prow = hf * 64 + (warp & 3) * 16;
    attention(sb, qf, b, tile, lane, g_o[cta] + tile * 2048 + q4 * 128 + g * 16, tag, &g_flag[cta][1], pm0, pm1);
    stg64_if(&g_om[cta][tile * 8 + g], tagw(__float_as_uint(pm0), tag, 1), __float_as_uint(pm1), q4 == 0);
    NEW_PHASE();
    PROFT(0, 6);
    asm volatile("barrier.cluster.wait.acquire.aligned;" ::: "memory");
    if (lane == 0) mbar_arrive_remote(mapa(bar(B_PEER), peer));
    uint32_t xres[16];
    {
      const __nv_bfloat16* xs = p.x + (size_t)(b * 128 + prow + g) * DM + (kb0 + wg) * 64 + q4 * 2;
#pragma unroll
      for (int i = 0; i < 8; i++) { xres[2 * i] = ldg32_nc(xs + i * 8); xres[2 * i + 1] = ldg32_nc(xs + 8 * DM + i * 8); }
    }
    {
      float acc[32];
      mbar_wait(bar(B_WO), 0);
      const uint64_t dwo = mkdesc(sb + wopiece(wg, 1), 8192, 1024, 1), dao = mkdesc(sb + SM_O, 128, 1024, 0);
#pragma unroll
      for (int i = 0; i < 16; i++) { acc[2 * i] = bf_lo(xres[i]); acc[2 * i + 1] = bf_hi(xres[i]); }
      pin(acc);
      bool bad = false;
      const uint2* mp = &g_om[b * 8 + q4 * 2][(prow >> 1) + g];
      uint2 u0 = make_uint2(0u, 0u), u1 = u0;
      float acc2[32];
      uint32_t bad2 = 0;
#pragma unroll
      for (int i = 0; i < 4; i++) {
        mbar_wait(bar(B_FULLA + 4 + i), 0);
        if (i == 0) PROFT(0, 7);
        wg_fence();
#pragma unroll
        for (int k = 8 * i; k < 8 * i + 8; k++) {
          if (k < 16) wgmma_ss_n64(acc, dao + (k >> 2) * 512 + (k & 3) * 16, dwo + 4096 + k * 128, 1);
          else wgmma_ss_n64(acc2, dao + (k >> 2) * 512 + (k & 3) * 16, dwo + (k & 15) * 128, k != 16);
          if (k == 10) bad = __any_sync(0xffffffffu, stale_smem<8>(sb + SM_O + tid * 16 + (lane >> 3) * 4, 4096, tag) != 0);
          if (k == 26) { bad2 = stale_smem<8>(sb + SM_O + 32768 + tid * 16 + (lane >> 3) * 4, 4096, tag); u0 = ldg64_ll(mp); u1 = ldg64_ll(mp + 64); }
          if (k == 17) {
            wg_commit();
            wg_wait<1>();
            if (lane == 0 && !bad) mbar_arrive(bar(B_OHALF));
            wg_fence();
          }
        }
        wg_commit();
      }
      mbar_wait(bar(B_PEER), 0);
      const bool redo = nb_any(NB_CONS, 256, bad || bad2);
      wg_wait<0>();
      pin(acc); pin(acc2);
      if (__builtin_expect(redo, 0)) {
        CNT(0);
        const int s0 = nb_any(NB_CONS, 256, bad) ? 0 : 4;
        repair(sb + SM_O + s0 * 8192 + tid * 16, g_o[b * 8 + s0] + hf * 8192 + tid * 16, 8 - s0, 8192, 16384, tag);
        repair(sb + SM_O + s0 * 8192 + 4096 + tid * 16, g_o[b * 8 + s0] + hf * 8192 + 4096 + tid * 16, 8 - s0, 8192, 16384, tag);
        nb_sync(NB_CONS, 256);
#pragma unroll 1
        for (int s = s0; s < 8; s++) {
          wg_fence();
#pragma unroll
          for (int k = 0; k < 4; k++) wgmma_ss_n64(acc2, dao + s * 512 + k * 16, dwo + (s < 4 ? 4096 : 0) + ((s & 3) * 4 + k) * 128, s != s0 || k != 0);
          wg_commit();
          wg_wait<0>();
        }
        pin(acc2);
        if (s0 == 0) {
#pragma unroll
          for (int i = 0; i < 16; i++) {
            asm volatile("add.u32 %0, %0, 0;" : "+r"(xres[i]));
            acc[2 * i] = bf_lo(xres[i]); acc[2 * i + 1] = bf_hi(xres[i]);
          }
        }
        nb_sync(NB_CONS, 256);
        if (lane == 0 && bad) mbar_arrive(bar(B_OHALF));
      }
      PROFT(0, 8);
      for (int it = 0; __any_sync(0xffffffffu, ((u0.x ^ tag) | (u1.x ^ tag)) & 1) && it < (1 << 17); it++) { CNT(5); u0 = ldg64_ll(mp); u1 = ldg64_ll(mp + 64); }
      __syncwarp();
      float s0 = __uint_as_float(u0.x) + __uint_as_float(u1.x), s1 = __uint_as_float(u0.y) + __uint_as_float(u1.y);
      s0 += __shfl_xor_sync(0xffffffffu, s0, 1); s1 += __shfl_xor_sync(0xffffffffu, s1, 1);
      s0 += __shfl_xor_sync(0xffffffffu, s0, 2); s1 += __shfl_xor_sync(0xffffffffu, s1, 2);
      const uint32_t hoff = wg * 16384 + prow * 128 + lane * 4;
      const uint32_t sh = sb + SM_HE + hoff;
#pragma unroll
      for (int i = 0; i < 8; i++) {
        xres[2 * i] = tagw(pack_bf16((acc[4 * i] + acc2[4 * i]) - s0, (acc[4 * i + 1] + acc2[4 * i + 1]) - s0), tag, q4 == (i & 3));
        xres[2 * i + 1] = tagw(pack_bf16((acc[4 * i + 2] + acc2[4 * i + 2]) - s1, (acc[4 * i + 3] + acc2[4 * i + 3]) - s1), tag, q4 == (i & 3));
        sts32(sh + i * 128, xres[2 * i]); sts32(sh + 1024 + i * 128, xres[2 * i + 1]);
      }
      PROFT(0, 30);
      fence_async_smem();
      __syncwarp();
      PROFT(0, 26);
      if (elect_one()) {
        const uint32_t sw = sb + SM_HE + wg * 16384 + prow * 128;
        bulk_s2g(g_h[b * 8 + kb0] + wg * 16384 + prow * 128, sw, 2048);
        bulk_s2peer(mapa(sw, peer), sw, 2048, mapa(bar(B_RECV), peer));
        mbar_arrive(bar(B_ODONE));
      }
      __syncwarp();
      PROFT(0, 24);
      PROFT(0, 18);
      float qa[4] = {0.f, 0.f, 0.f, 0.f}, qb[4] = {0.f, 0.f, 0.f, 0.f};
#pragma unroll
      for (int k = 0; k < 8; k++) { mma_k8(qa, xres[2 * k], xres[2 * k + 1], xres[2 * k]); mma_k8(qb, xres[2 * k], xres[2 * k + 1], xres[2 * k + 1]); }
      stg128_if(&g_stat2[b * 8 + kb0 + wg][(prow >> 1) + g], tagw(__float_as_uint(s0), tag, 1), __float_as_uint((g & 1) ? qa[1] : qa[0]), __float_as_uint(s1),
                  __float_as_uint((g & 1) ? qb[3] : qb[2]), q4 == (g >> 1));
      red_lane0(&g_flag[cta][2], lane);
      PROFT(0, 21);
      nb_sync(NB_CONS, 256);
      if (wg != hf) mbar_wait(bar(B_RECV), 0);
    }
    NEW_PHASE();
    PROFT(0, 9);
    uint32_t own[56];
    float2 st0, st1;
    float accC[96], accA[64];
    float accB[64];
    {
      {
        const uint64_t da = mkdesc(sb + aslot(0) + wg * 8192, 128, 1024, 0);
        const uint64_t db = mkdesc(sb + cslot(1), 16384, 1024, 1), dc = mkdesc(sb + cstage(0), 4096, 512, 2);
        mbar_wait(bar(B_FULLS), 0);
        wg_fence();
#pragma unroll
        for (int k = 0; k < 8; k++) wgmma_ss_n128(accA, da + (k >> 2) * 1024 + (k & 3) * 16, db + k * 128, k != 0);
        wg_commit();
        mbar_wait(bar(B_FULLS + 1), 0);
        wg_fence();
#pragma unroll
        for (int k = 0; k < 4; k++) wgmma_ss_n192(accC, da + k * 16, dc + k * 64, k != 0);
        wg_commit();
        wg_wait<1>();
        pin(accA);
        if (lane == 0) mbar_arrive(bar(B_DONES));
      }
      const uint4* sp = &g_stat2[b * 8 + q4 * 2][warp * 8 + g];
      uint4 t0 = make_uint4(0u, 0u, 0u, 0u), t1 = t0;
      PROFT(0, 31);
#pragma unroll
      for (int kp = 1; kp < 8; kp++) {
        if (kp >= 2) mbar_wait(bar(B_HV + 2 * (kp - 2) + wg), 0);
        if (kp == 2) PROFT(0, 20);
        mbar_wait(bar(B_FULLS + 1 + kp), 0);
        if (kp == 2) PROFT(0, 4);
        if (kp == 4) PROFT(0, 10);
        wg_fence();
        const uint64_t da = mkdesc(sb + aslot(kp >> 1) + (kp & 1) * 16384 + wg * 8192, 128, 1024, 0);
        const uint64_t db = mkdesc(sb + cstage(kp), 4096, 512, 2);
#pragma unroll
        for (int k = 0; k < 4; k++) wgmma_ss_n192(accC, da + k * 16, db + k * 64, 1);
        wg_commit();
        if (kp == 5) { t0 = ldg128_ll(sp); t1 = ldg128_ll(sp + 64); }
        wg_wait<1>();
        if (lane == 0) { mbar_arrive(bar(B_DONES + kp)); if (kp == 3) mbar_arrive_remote(mapa(bar(B_DONES + 3), peer)); }
      }
#pragma unroll
      for (int n = 9; n < 16; n++) {
        const int m = n & 3;
        NEW_PHASE();
        mbar_wait(bar(B_FULLC + n % 3), (n / 3 + 1) & 1);
        const uint64_t da = mkdesc(sb + aslot(m) + wg * 8192, 128, 1024, 0);
        const uint64_t db = mkdesc(sb + cslot(n % 3), 16384, 1024, 1);
#pragma unroll
        for (int k2 = 0; k2 < 4; k2++) {
          wg_fence();
#pragma unroll
          for (int k = 2 * k2; k < 2 * k2 + 2; k++) {
            if (n < 12) wgmma_ss_n128(accA, da + (k >> 2) * 1024 + (k & 3) * 16, db + k * 128, 1);
            else wgmma_ss_n128(accB, da + (k >> 2) * 1024 + (k & 3) * 16, db + k * 128, (m | k) != 0);
          }
          if (k2 == 0 || k2 == 3) wg_commit();
          if (k2 == 0) {
            wg_wait<1>();
            if (lane == 0) {
              mbar_arrive(bar(n == 9 ? B_DONES + 8 : B_EMPTYC + (n - 1) % 3));
              if (n >= 13) mbar_arrive(bar(B_EMPTYA + n - 13));
              if (n == 13) mbar_arrive_remote(mapa(bar(B_PEER), peer));
              if (n == 14) mbar_arrive_remote(mapa(bar(B_CDONE), peer));
            }
            if (n == 9) {
              pin(accC);
              PROFT(0, 11);
      {
        for (int it = 0; __any_sync(0xffffffffu, ((t0.x ^ tag) | (t1.x ^ tag)) & 1) && it < (1 << 17); it++) { CNT(4); t0 = ldg128_ll(sp); t1 = ldg128_ll(sp + 64); }
        __syncwarp();
        const float m0 = __uint_as_float(t0.x), m1 = __uint_as_float(t0.z);
        float v0 = __uint_as_float(t0.y) + __uint_as_float(t1.y), v1 = __uint_as_float(t0.w) + __uint_as_float(t1.w);
        v0 += __shfl_xor_sync(0xffffffffu, v0, 1); v1 += __shfl_xor_sync(0xffffffffu, v1, 1);
        v0 += __shfl_xor_sync(0xffffffffu, v0, 2); v1 += __shfl_xor_sync(0xffffffffu, v1, 2);
        st0 = make_float2(m0, __fdividef(1.f, v0 * (1.f / DM) + LN_EPS));
        st1 = make_float2(m1, __fdividef(1.f, v1 * (1.f / DM) + LN_EPS));
      }
            }
            if (n == 12) { pin(accA); PROFT(0, 12); }
          }
          if (n < 12) {
            const int i = (n - 9) * 4 + k2;
            reglu_block(&accC[4 * i], &accC[48 + 4 * i], own[2 * i], own[2 * i + 1]);
          } else if (n < 14) {
            const int i = m * 4 + k2;
            reglu_block(&accA[4 * i], &accA[32 + 4 * i], own[24 + 2 * i], own[25 + 2 * i]);
          }
          if (n >= 13 && (n - 13) * 4 + k2 >= 2) {
            const int v = (n - 13) * 4 + k2 - 2;
            if (v == 0) mbar_wait(bar(B_PEER), 1);
            if (v == 6) mbar_wait(bar(B_CDONE), 0);
            const uint32_t rb = mapa(sb, peer);
            st_async128(rb + (v < 6 ? aslot(0) + v * 4096 : aslot(1) + (v - 6) * 4096) + tid * 16, &own[4 * v], rb + SM_BAR + B_RECV * 8);
          }
        }
      }
    }
    NEW_PHASE();
    {
      uint32_t oth[56];
      float accP[32];
      float accQ[32];
      auto krow = [](int v, int e) { return v < 6 ? (e ? 0 : 128) + v * 16 : e * 96 + (v - 6) * 16; };
      {
        const uint64_t d0 = mkdesc(sb + cslot(1), 8192, 1024, 1), d1 = mkdesc(sb + aslot(2), 8192, 1024, 1);
        const uint32_t rb = mapa(sb, peer);
        mbar_wait(bar(B_FULLC + 1), 0);
#pragma unroll
        for (int c = 0; c < 6; c++) {
          if (c == 2 || c == 4) {
            if (c == 2) mbar_wait(bar(B_RECV), 1);
#pragma unroll
            for (int v = (c == 2 ? 0 : 6); v < (c == 2 ? 6 : 10); v++) {
              const uint4 t = lds128(sb + (v < 6 ? aslot(0) + v * 4096 : aslot(1) + (v - 6) * 4096) + tid * 16);
              oth[4 * v] = t.x; oth[4 * v + 1] = t.y; oth[4 * v + 2] = t.z; oth[4 * v + 3] = t.w;
            }
            if (c == 2) {
              __syncwarp();
              if (lane == 0) mbar_arrive(bar(B_EMPTYA + 0));
              mbar_wait(bar(B_FULLW + 2), 1);
            }
          }
          wg_fence();
#pragma unroll
          for (int e = 0; e < 4; e++) {
            const int x = c * 4 + e;
            if (x < 10) wgmma_rs_n64(accP, own[4 * x], own[4 * x + 1], own[4 * x + 2], own[4 * x + 3], d0 + krow(x, hf) * 8, x != 0);
            else if (x < 20) wgmma_rs_n64(accP, oth[4 * x - 40], oth[4 * x - 39], oth[4 * x - 38], oth[4 * x - 37], d1 + krow(x - 10, hf ^ 1) * 8, 1);
            else wgmma_rs_n64(accP, own[4 * x - 40], own[4 * x - 39], own[4 * x - 38], own[4 * x - 37], d0 + krow(x - 10, hf) * 8, 1);
          }
          if (c == 0) {
            wg_commit();
            wg_wait<1>();
            pin(accB);
            if (lane == 0) { mbar_arrive(bar(B_EMPTYC + 0)); mbar_arrive(bar(B_EMPTYA + 3)); }
            PROFT(0, 13);
          }
          if (c < 4) {
#pragma unroll
            for (int i = 2 * c; i < 2 * c + 2; i++)
              reglu_block(&accB[4 * i], &accB[32 + 4 * i], own[40 + 2 * i], own[41 + 2 * i]);
            st_async128(rb + aslot(1) + 16384 + c * 4096 + tid * 16, &own[40 + 4 * c], rb + SM_BAR + B_WO * 8);
          }
        }
      }
      PROFT(0, 14);
      float sum[32];
      uint32_t early_bad = 0;
      uint4 pt[4];
      auto addp = [&]() {
#pragma unroll
        for (int i = 0; i < 4; i++) {
          const float r0 = st0.y, r1 = st1.y;
          sum[8 * i] += bf_lo(pt[i].x) * r0; sum[8 * i + 1] += bf_hi(pt[i].x) * r0; sum[8 * i + 2] += bf_lo(pt[i].y) * r1; sum[8 * i + 3] += bf_hi(pt[i].y) * r1;
          sum[8 * i + 4] += bf_lo(pt[i].z) * r0; sum[8 * i + 5] += bf_hi(pt[i].z) * r0; sum[8 * i + 6] += bf_lo(pt[i].w) * r1; sum[8 * i + 7] += bf_hi(pt[i].w) * r1;
        }
      };
#define psrc (g_p[cta][0] + warp * 2048 + lane * 16)
#pragma unroll
      for (int s = 1; s < 4; s++) {
        NEW_PHASE();
        const uint32_t w0 = (s == 1) ? cslot(2) : (s == 2 ? cslot(0) : aslot(1)), w1 = (s == 1) ? aslot(3) : (s == 2 ? aslot(0) : cslot(1));
        const uint64_t d0 = mkdesc(sb + w0, 8192, 1024, 1), d1 = mkdesc(sb + w1, 8192, 1024, 1);
        uint8_t* gp = g_p[b * 8 + ((pi + s) & 3) * 2 + hf][s - 1] + warp * 2048;
        const int cship = (s == 1) ? 3 : 0;
#pragma unroll
        for (int c = 0; c < 7; c++) {
          if (c == 0) {
            if (s == 1) mbar_wait(bar(B_FULLC + 2), 0);
            if (s == 2) mbar_wait(bar(B_FULLC + 0), 1);
            if (s == 3) mbar_wait(bar(B_FULLW + 1), 1);
          }
          if (c == 3) {
            if (s == 1) mbar_wait(bar(B_FULLW + 3), 1);
            if (s == 2) mbar_wait(bar(B_FULLW + 0), 1);
            if (s == 3) mbar_wait(bar(B_FULLC + 1), 1);
          }
          if (c == 0 || c == 3 || (s == 3 && c == 5)) wg_fence();
#pragma unroll
          for (int e = 0; e < 4; e++) {
            const int x = c * 4 + e;
            if (s & 1) {
              if (x < 14) wgmma_rs_n64(accQ, own[4 * x], own[4 * x + 1], own[4 * x + 2], own[4 * x + 3], d0 + krow(x, hf) * 8, x != 0);
              else wgmma_rs_n64(accQ, oth[4 * x - 56], oth[4 * x - 55], oth[4 * x - 54], oth[4 * x - 53], d1 + krow(x - 14, hf ^ 1) * 8, 1);
            } else {
              if (x < 14) wgmma_rs_n64(accP, own[4 * x], own[4 * x + 1], own[4 * x + 2], own[4 * x + 3], d0 + krow(x, hf) * 8, x != 0);
              else wgmma_rs_n64(accP, oth[4 * x - 56], oth[4 * x - 55], oth[4 * x - 54], oth[4 * x - 53], d1 + krow(x - 14, hf ^ 1) * 8, 1);
            }
          }
          if (s == 1 && c == 2) {
            mbar_wait(bar(B_WO), 1);
#pragma unroll
            for (int v = 10; v < 14; v++) {
              const uint4 t = lds128(sb + aslot(1) + (v - 6) * 4096 + tid * 16);
              oth[4 * v] = t.x; oth[4 * v + 1] = t.y; oth[4 * v + 2] = t.z; oth[4 * v + 3] = t.w;
            }
            __syncwarp();
            if (lane == 0) mbar_arrive(bar(B_EMPTYA + 1));
            const uint64_t dz = mkdesc(sb + aslot(2), 8192, 1024, 1);
            wg_fence();
#pragma unroll
            for (int v = 10; v < 14; v++) wgmma_rs_n64(accP, oth[4 * v], oth[4 * v + 1], oth[4 * v + 2], oth[4 * v + 3], dz + krow(v, hf ^ 1) * 8, 1);
            wg_commit();
          }
          if (c == cship || c == 6) wg_commit();
          if (c == cship) {
            wg_wait<1>();
            if (s & 1) pin(accP); else pin(accQ);
            if (s == 1 && lane == 0) { mbar_arrive(bar(B_EMPTYC + 1)); mbar_arrive(bar(B_EMPTYA + 2)); }
            if (s == 2 && lane == 0) mbar_arrive(bar(B_EMPTYA + 3));
            const float* a = (s & 1) ? accP : accQ;
            if (s >= TS0) {
              mbar_wait(bar(B_EMPTYA + 3), 1);
              const uint32_t stg = sb + cslot(2) + (s - 2) * 16384 + warp * 2048;
#pragma unroll
              for (int i = 0; i < 4; i++)
                sts128(stg + i * 512 + lane * 16, make_uint4(tagw(pack_bf16(a[8 * i], a[8 * i + 1]), tag, 1), pack_bf16(a[8 * i + 2], a[8 * i + 3]),
                                                            pack_bf16(a[8 * i + 4], a[8 * i + 5]), pack_bf16(a[8 * i + 6], a[8 * i + 7])));
              fence_async_smem();
              __syncwarp();
              if (elect_one()) bulk_s2g(gp, stg, 2048);
              __syncwarp();
            } else {
#pragma unroll
              for (int i = 0; i < 4; i++)
                stg128_ll(gp + i * 512 + lane * 16, tagw(pack_bf16(a[8 * i], a[8 * i + 1]), tag, 1), pack_bf16(a[8 * i + 2], a[8 * i + 3]),
                          pack_bf16(a[8 * i + 4], a[8 * i + 5]), pack_bf16(a[8 * i + 6], a[8 * i + 7]));
              if (s < 3) red_lane0(&g_flag[b * 8 + ((pi + s) & 3) * 2 + hf][3 + s], lane);
            }
            PROFT(0, 26 + s);
          }
          if (s == 2 && TS0 <= 2 && c == 2 && lane == 0) red_relaxed(&g_flag[b * 8 + ((pi + s) & 3) * 2 + hf][3 + s]);
          if (s == 3 && c == 4) {
            mbar_wait(bar(B_FULLA), 0);
            uint4 pu[4];
#pragma unroll
            for (int i = 0; i < 4; i++) { pt[i] = lds128(sb + aslot(2) + 16384 + warp * 2048 + i * 512 + lane * 16); pu[i] = lds128(sb + aslot(2) + 32768 + warp * 2048 + i * 512 + lane * 16); }
            early_bad = stale<4>(pt, tag) | stale<4>(pu, tag);
#pragma unroll
            for (int i = 0; i < 4; i++) {
              const uint32_t w[4] = {pt[i].x, pt[i].y, pt[i].z, pt[i].w}, u[4] = {pu[i].x, pu[i].y, pu[i].z, pu[i].w};
#pragma unroll
              for (int e = 0; e < 4; e++) {
                const float rs = (e & 1) ? st1.y : st0.y, mu = (e & 1) ? st1.x : st0.x;
                const uint32_t hr = lds32(sb + aslot(2) + warp * 2048 + (e & 1) * 1024 + (2 * i + (e >> 1)) * 128 + lane * 4);
                sum[8 * i + 2 * e] = (bf_lo(w[e]) + bf_lo(u[e])) * rs + (bf_lo(hr) + mu);
                sum[8 * i + 2 * e + 1] = (bf_hi(w[e]) + bf_hi(u[e])) * rs + (bf_hi(hr) + mu);
              }
            }
            pin(sum);
          }
          if (s == 3 && c == 5) {
#pragma unroll
            for (int i = 0; i < 4; i++) pt[i] = ldg128_ll(psrc + 32768 + i * 512);
          }
        }
      }
      PROFT(0, 15);
      wg_wait<0>();
      pin(accQ);
      if (__any_sync(0xffffffffu, (early_bad | stale<4>(pt, tag)) != 0)) {
        if (early_bad) {
          CNT(2);
#pragma unroll
          for (int i = 0; i < 16; i++) {
            const uint32_t hr = lds32(sb + aslot(2) + warp * 2048 + (i & 1) * 1024 + (i >> 1) * 128 + lane * 4);
            sum[2 * i] = bf_lo(hr) + ((i & 1) ? st1.x : st0.x); sum[2 * i + 1] = bf_hi(hr) + ((i & 1) ? st1.x : st0.x);
          }
        }
#pragma unroll 1
        for (int q = early_bad ? 0 : 2; q < 3; q++) {
          int it = 0;
          do {
            CNT(3);
#pragma unroll
            for (int i = 0; i < 4; i++) pt[i] = ldg128_ll(psrc + q * 16384 + i * 512);
          } while (stale<4>(pt, tag) && ++it < (1 << 17));
          if (q < 2) addp();
        }
      }
      addp();
      __syncwarp();
      PROFT(0, 25);
      __nv_bfloat16* outp = p.out + (size_t)(b * 128 + warp * 16 + g) * DM + hf * 256 + pi * 64 + (q4 & 1) * 8 + (q4 >> 1) * 4;
      const bool odd = tid & 1;
#pragma unroll
      for (int i = 0; i < 8; i += 2) {
        uint32_t w[2][2];
#pragma unroll
        for (int e = 0; e < 2; e++) {
          const int x = 4 * (i + e);
          w[e][0] = pack_bf16(accQ[x] * st0.y + sum[x], accQ[x + 1] * st0.y + sum[x + 1]);
          w[e][1] = pack_bf16(accQ[x + 2] * st1.y + sum[x + 2], accQ[x + 3] * st1.y + sum[x + 3]);
        }
#pragma unroll
        for (int r = 0; r < 2; r++) {
          const uint32_t got = __shfl_xor_sync(0xffffffffu, odd ? w[0][r] : w[1][r], 1);
          stg64(outp + r * 8 * DM + i * 8, odd ? got : w[0][r], odd ? w[1][r] : got);
        }
      }
    }
    asm volatile("cp.async.bulk.wait_group 0;" ::: "memory");
    PROFT(0, 16);
  }
}
#undef lane
#undef g
#undef q4
#undef psrc

typedef CUresult (*EncodeFn)(CUtensorMap*, CUtensorMapDataType, cuuint32_t, void*, const cuuint64_t*, const cuuint64_t*, const cuuint32_t*,
                             const cuuint32_t*, CUtensorMapInterleave, CUtensorMapSwizzle, CUtensorMapL2promotion, CUtensorMapFloatOOBfill);

void make_map(EncodeFn enc, CUtensorMap* m, const void* ptr, int rank, uint64_t d0, uint64_t d1, uint64_t d2, uint64_t s1, uint64_t s2,
              uint32_t b0, uint32_t b1, uint32_t b2, CUtensorMapSwizzle sw) {
  cuuint64_t gd[3] = {d0, d1, d2};
  cuuint64_t gs[2] = {s1, s2};
  cuuint32_t bd[3] = {b0, b1, b2};
  cuuint32_t es[3] = {1, 1, 1};
  enc(m, CU_TENSOR_MAP_DATA_TYPE_BFLOAT16, rank, const_cast<void*>(ptr), gd, gs, bd, es, CU_TENSOR_MAP_INTERLEAVE_NONE, sw,
      CU_TENSOR_MAP_L2_PROMOTION_L2_128B, CU_TENSOR_MAP_FLOAT_OOB_FILL_NONE);
}

}

extern "C" void kernel_launch(void* const* d_in, const int* in_sizes, int n_in, void* d_out, int out_size) {
  (void)in_sizes; (void)n_in; (void)out_size;
  static EncodeFn enc = nullptr;
  if (!enc) {
    void* f = nullptr;
    cudaDriverEntryPointQueryResult qr;
    cudaGetDriverEntryPoint("cuTensorMapEncodeTiled", &f, cudaEnableDefault, &qr);
    enc = (EncodeFn)f;
    cudaFuncSetAttribute(fused_block_kernel, cudaFuncAttributeMaxDynamicSharedMemorySize, SMEM_TOTAL);
  }
  Params p;
  p.x = (const __nv_bfloat16*)d_in[0];
  p.wqkv = (const __nv_bfloat16*)d_in[1];
  p.wo = (const __nv_bfloat16*)d_in[2];
  p.wg = (const __nv_bfloat16*)d_in[4];
  p.wu = (const __nv_bfloat16*)d_in[5];
  p.wd = (const __nv_bfloat16*)d_in[6];
  p.out = (__nv_bfloat16*)d_out;
  make_map(enc, &p.tm_x, p.x, 2, DM, SEQ, 1, DM * 2, 0, 64, 128, 1, CU_TENSOR_MAP_SWIZZLE_128B);
  make_map(enc, &p.tm_qkv, p.wqkv, 2, 1536, 512, 1, 3072, 0, 64, 128, 1, CU_TENSOR_MAP_SWIZZLE_128B);
  {
    cuuint64_t gd[5] = {512, 2, 4, 4, 16};
    cuuint64_t gs[4] = {1024, 8 * 1024, 2 * 1024, 32 * 1024};
    cuuint32_t bd[5] = {64, 2, 4, 4, 8};
    cuuint32_t es[5] = {1, 1, 1, 1, 1};
    enc(&p.tm_wo, CU_TENSOR_MAP_DATA_TYPE_BFLOAT16, 5, const_cast<__nv_bfloat16*>(p.wo), gd, gs, bd, es, CU_TENSOR_MAP_INTERLEAVE_NONE,
        CU_TENSOR_MAP_SWIZZLE_128B, CU_TENSOR_MAP_L2_PROMOTION_L2_128B, CU_TENSOR_MAP_FLOAT_OOB_FILL_NONE);
  }
  make_map(enc, &p.tm_g1, p.wg, 2, FF, 512, 1, FF * 2, 0, 64, 128, 1, CU_TENSOR_MAP_SWIZZLE_128B);
  make_map(enc, &p.tm_u1, p.wu, 2, FF, 512, 1, FF * 2, 0, 64, 128, 1, CU_TENSOR_MAP_SWIZZLE_128B);
  make_map(enc, &p.tm_g2, p.wg, 3, FF, 512, 3, FF * 2, 64, 32, 64, 3, CU_TENSOR_MAP_SWIZZLE_64B);
  make_map(enc, &p.tm_u2, p.wu, 3, FF, 512, 3, FF * 2, 64, 32, 64, 3, CU_TENSOR_MAP_SWIZZLE_64B);
  make_map(enc, &p.tm_d, p.wd, 2, DM, FF, 1, DM * 2, 0, 64, 224, 1, CU_TENSOR_MAP_SWIZZLE_128B);
  fused_block_kernel<<<NCTA, 384, SMEM_TOTAL>>>(p);
}
```
